```python
import torch

def _softmax(x, axis=-1):
    return torch.softmax(x, dim=axis)
def _gelu(x):
    return torch.nn.functional.gelu(x, approximate="tanh")
def _silu(x):
    return torch.nn.functional.silu(x)
def _sigmoid(x):
    return torch.sigmoid(x)
def _layernorm(x, axis=-1, eps=1e-5):
    m = x.mean(dim=axis, keepdim=True)
    v = x.var(dim=axis, keepdim=True, unbiased=False)
    return (x - m) / torch.sqrt(v + eps)
def _scatter_add(tgt, idx, src, axis=0):
    return tgt.clone().index_add_(axis, idx, src)
def _segment_sum(src, seg, n):
    out = torch.zeros((n,) + src.shape[1:], dtype=src.dtype)
    return out.index_add_(0, seg, src)
def _pad(x, pw):
    flat = tuple(v for pair in reversed(pw) for v in pair)
    return torch.nn.functional.pad(x, flat)

kernel_name = 'concat_heads__compressed_kv_cla__gqa_block_cached__decode'

def setup_inputs():

    _w = (lambda a: (lambda t: t.to(torch.bfloat16) if t.is_floating_point() else t)(torch.as_tensor(a)))
    def _A_setup():
        B, H, Sq, Sk, D, M = 2, 32, 1, 4096, 128, 512
        Dc = 4 * D
        return {
            "x": _w((lambda *s: torch.randn(*s, dtype=torch.bfloat16) * 3.2)(B, Sq, M)),
            "c_kv": _w((lambda *s: torch.randn(*s, dtype=torch.bfloat16) * 0.1)(B, Sk, Dc)),
            "w_q": _w((lambda *s: torch.randn(*s, dtype=torch.bfloat16) * 6.4)(M, H, D) * (M ** -0.5)),
            "w_uk": _w((lambda *s: torch.randn(*s, dtype=torch.bfloat16) * 6.4)(Dc, H, D) * (Dc ** -0.5)),
            "w_uv": _w((lambda *s: torch.randn(*s, dtype=torch.bfloat16) * 0.1)(Dc, H, D) * (Dc ** -0.5)),
            "w_o": _w((lambda *s: torch.randn(*s, dtype=torch.bfloat16) * 0.1)(H, D, M) * ((H * D) ** -0.5)),
        }
    _A_in = _A_setup()

    def _B_setup():
        B, Sq, D = 2, 1, 512
        Hq, Hkv, Sk, Dh = 32, 32, 4096, 128
        assert Hq % Hkv == 0, (Hq, Hkv)
        return {
            "x": _w((lambda *s: torch.randn(*s, dtype=torch.bfloat16) * 1.6)(B, Sq, D)),
            "k_cache": _w((lambda *s: torch.randn(*s, dtype=torch.bfloat16) * 1.6)(B, Hkv, Sk, Dh)),
            "v_cache": _w((lambda *s: torch.randn(*s, dtype=torch.bfloat16) * 0.05)(B, Hkv, Sk, Dh)),
            "wq": _w((lambda *s: torch.randn(*s, dtype=torch.bfloat16) * 1.6)(D, Hq * Dh) * (D ** -0.5)),
            "wo": _w((lambda *s: torch.randn(*s, dtype=torch.bfloat16) * 0.05)(Hq * Dh, D) * ((Hq * Dh) ** -0.5)),
        }
    _B_in = _B_setup()

    return {
        "A_x": _A_in["x"],
        "A_c_kv": _A_in["c_kv"],
        "A_w_q": _A_in["w_q"],
        "A_w_uk": _A_in["w_uk"],
        "A_w_uv": _A_in["w_uv"],
        "A_w_o": _A_in["w_o"],
        "B_x": _B_in["x"],
        "B_k_cache": _B_in["k_cache"],
        "B_v_cache": _B_in["v_cache"],
        "B_wq": _B_in["wq"],
        "B_wo": _B_in["wo"],
    }

def reference(A_x, A_c_kv, A_w_q, A_w_uk, A_w_uv, A_w_o, B_x, B_k_cache, B_v_cache, B_wq, B_wo):
    def _A_ref(x, c_kv, w_q, w_uk, w_uv, w_o):
        B, Sq, M = x.shape[0], x.shape[1], x.shape[2]
        Sk = c_kv.shape[1]
        H, D = w_q.shape[1], w_q.shape[2]
        q = torch.einsum("bqm,mhd->bhqd", x, w_q)
        k = torch.einsum("bkc,chd->bhkd", c_kv, w_uk)
        v = torch.einsum("bkc,chd->bhkd", c_kv, w_uv)
        scores = torch.einsum("bhqd,bhkd->bhqk", q, k) * (D ** -0.5)
        off = Sk - Sq
        qi = torch.arange(Sq)[:, None]
        kj = torch.arange(Sk)[None, :]
        cmask = kj <= (qi + off)
        scores = torch.where(cmask[None, None], scores, -1e9)
        p = _softmax(scores, axis=-1)
        ctx = torch.einsum("bhqk,bhkd->bhqd", p, v)
        return torch.einsum("bhqd,hdm->bqm", ctx, w_o)

    def _B_ref(x, k_cache, v_cache, wq, wo):
        B, Sq, D = x.shape
        Hq, Dh = 32, 128
        Hkv = k_cache.shape[1]
        rep = Hq // Hkv
        q = (lambda x, *d: x.permute(*d))((x @ wq).reshape(B, Sq, Hq, Dh), 0, 2, 1, 3)
        k = (lambda x, n, axis: torch.repeat_interleave(x, n, dim=axis))(k_cache, rep, axis=1)
        v = (lambda x, n, axis: torch.repeat_interleave(x, n, dim=axis))(v_cache, rep, axis=1)
        scores = torch.einsum("bhqd,bhkd->bhqk", q, k) * (Dh ** -0.5)
        p = _softmax(scores, axis=-1)
        o = torch.einsum("bhqk,bhkd->bhqd", p, v)
        return (lambda x, *d: x.permute(*d))(o, 0, 2, 1, 3).reshape(B, Sq, Hq * Dh) @ wo

    a = _A_ref(A_x, A_c_kv, A_w_q, A_w_uk, A_w_uv, A_w_o)
    b = _B_ref(B_x, B_k_cache, B_v_cache, B_wq, B_wo)
    return torch.concatenate([a, b], axis=-1)
```

```cpp
#include <cuda_runtime.h>
#include <cuda.h>
#include <cuda_bf16.h>
#include <stdint.h>

#define RING 7
#define WIN 4
#define WHI 5
#define THETA 64
#define END_V 40
#define GATE_W 64
#define PREWIN 2
#define TAILWIN 3
#define POLL_DELAY 2500
#define POLL_DELAY2 4000
#define ST_SPLIT 8
#define ST_GAP 500
#define BACKOFF 200
#define BACKOFF2 100

namespace {

constexpr int NCTA = 128;
constexpr int NTHREADS = 448;
constexpr uint32_t CH = 16384;
constexpr int NTILE = 32;

constexpr uint32_t OFF_RING = 0;
constexpr uint32_t OFF_S0 = RING * CH;
constexpr uint32_t OFF_S1 = OFF_S0 + 2 * CH;
constexpr uint32_t OFF_S2 = OFF_S1 + 2 * CH;
constexpr uint32_t OFF_P = OFF_S2 + 2 * CH;
constexpr uint32_t OFF_SC = OFF_P + 4096;
constexpr uint32_t VROW = 272;
constexpr uint32_t OFF_XB = OFF_SC + 8704;
constexpr uint32_t OFF_XA = OFF_XB + 2 * VROW;
constexpr uint32_t OFF_QA = OFF_XA + 2 * VROW;
constexpr uint32_t OFF_QS = OFF_QA + 2 * VROW;
constexpr uint32_t OFF_CC = OFF_QS + 2 * VROW;
constexpr uint32_t OFF_CA = OFF_CC + 4 * VROW;
constexpr uint32_t OFF_OB = OFF_CA + 2 * VROW;
constexpr uint32_t OFF_QB = OFF_OB + 2 * VROW;
constexpr uint32_t OFF_LSE = OFF_QB + 256;
constexpr uint32_t OFF_ML = OFF_LSE + 512;
constexpr uint32_t OFF_TAG = OFF_ML + 32;
constexpr uint32_t OFF_NOW = OFF_TAG + 4;
constexpr uint32_t OFF_WIN = OFF_TAG + 8;
constexpr uint32_t OFF_TWIN = OFF_TAG + 12;
constexpr uint32_t OFF_BAR = OFF_TAG + 16;
constexpr int B_EMPTY = RING;
constexpr int B_WQB = 2 * RING;
constexpr int B_WQA = B_WQB + 2;
constexpr int B_WUK = B_WQA + 2;
constexpr int B_WUV = B_WUK + 2;
constexpr int B_CKV = B_WUV + 2;
constexpr int B_WO = B_CKV + 4;
constexpr int B_FREE = B_WO + 8;
constexpr int B_GATH = B_FREE + 1;
constexpr int B_S2 = B_GATH + 1;
constexpr int NBAR = B_S2 + 1;
constexpr uint32_t TS_OFF = OFF_BAR + NBAR * 8;
constexpr uint32_t SMEM_USED = TS_OFF;
constexpr uint32_t SMEM_BYTES = SMEM_USED + 1024;
static_assert(SMEM_BYTES <= 232448, "smem");
static_assert(RING >= WHI && WHI >= WIN && WIN >= 3 && WIN <= 6, "windows");

constexpr float LOG2E = 1.4426950408889634f;
constexpr float SCALE = 0.08838834764831845f;
#define SPIN_LOG 22
constexpr uint32_t SPIN_MAX = 1u << SPIN_LOG;

struct Maps { CUtensorMap wqB, wqA, wuk, wuv, woA, woB, ckv, ctxp; };

__device__ unsigned g_epoch;
__device__ __align__(256) unsigned g_cnt[96];
__device__ __align__(256) ulonglong2 g_e1[2][NCTA][128];
__device__ __align__(256) uint4 g_qabs[2 * 32 * 64];
__device__ __align__(256) uint4 g_ctxp[NCTA * 128 * 16];
__device__ __align__(256) float4 g_lse[32 * 32];
__device__ __align__(256) ulonglong2 g_e4[NCTA][128];
__device__ __align__(256) ulonglong2 g_e5[NCTA][128];
__device__ __align__(256) float4 g_acc[128][16];

#define TS(k) do {} while (0)

__device__ __forceinline__ void mbar_init(uint32_t b, int c) { asm volatile("mbarrier.init.shared::cta.b64 [%0], %1;" ::"r"(b), "r"(c) : "memory"); }
__device__ __forceinline__ void mbar_expect(uint32_t b, uint32_t bytes) { asm volatile("mbarrier.arrive.expect_tx.shared::cta.b64 _, [%0], %1;" ::"r"(b), "r"(bytes) : "memory"); }
__device__ __forceinline__ void mbar_arrive(uint32_t b) { asm volatile("mbarrier.arrive.shared::cta.b64 _, [%0];" ::"r"(b) : "memory"); }
__device__ __forceinline__ void mbar_wait(uint32_t b, uint32_t ph) {
    uint32_t ok, it = 0;
    do {
        asm volatile("{\n.reg .pred p;\nmbarrier.try_wait.parity.shared::cta.b64 p, [%1], %2;\nselp.u32 %0, 1, 0, p;\n}" : "=r"(ok) : "r"(b), "r"(ph) : "memory");
        if (++it > SPIN_MAX) __trap();
    } while (!ok);
}
__device__ __forceinline__ uint32_t mbar_test(uint32_t b, uint32_t ph) {
    uint32_t ok;
    asm volatile("{\n.reg .pred p;\nmbarrier.test_wait.parity.shared::cta.b64 p, [%1], %2;\nselp.u32 %0, 1, 0, p;\n}" : "=r"(ok) : "r"(b), "r"(ph) : "memory");
    return ok;
}
__device__ __forceinline__ void bulk1d(uint32_t dst, const void* src, uint32_t bar, uint64_t pol) {
    asm volatile("cp.async.bulk.shared::cluster.global.mbarrier::complete_tx::bytes.L2::cache_hint [%0], [%1], %2, [%3], %4;"
                 ::"r"(dst), "l"(src), "n"(CH), "r"(bar), "l"(pol) : "memory");
}
__device__ __forceinline__ void bulk1d_n(uint32_t dst, const void* src, uint32_t bytes, uint32_t bar) {
    asm volatile("cp.async.bulk.shared::cluster.global.mbarrier::complete_tx::bytes [%0], [%1], %2, [%3];"
                 ::"r"(dst), "l"(src), "r"(bytes), "r"(bar) : "memory");
}
__device__ __forceinline__ void tma3d(uint32_t dst, const CUtensorMap* map, int c1, int c2, uint32_t bar, uint64_t pol) {
    asm volatile("cp.async.bulk.tensor.3d.shared::cluster.global.mbarrier::complete_tx::bytes.L2::cache_hint [%0], [%1, {%3,%4,%5}], [%2], %6;"
                 ::"r"(dst), "l"(map), "r"(bar), "r"(0), "r"(c1), "r"(c2), "l"(pol) : "memory");
}
__device__ __forceinline__ void bar_sync(int id, int n) { asm volatile("barrier.cta.sync %0, %1;" ::"r"(id), "r"(n) : "memory"); }
__device__ __forceinline__ void bar_arrive(int id, int n) { asm volatile("barrier.cta.arrive %0, %1;" ::"r"(id), "r"(n) : "memory"); }
__device__ __forceinline__ void ldsm4(uint32_t (&r)[4], uint32_t a) {
    asm volatile("ldmatrix.sync.aligned.m8n8.x4.shared.b16 {%0,%1,%2,%3}, [%4];" : "=r"(r[0]), "=r"(r[1]), "=r"(r[2]), "=r"(r[3]) : "r"(a) : "memory");
}
__device__ __forceinline__ void ldsm4t(uint32_t (&r)[4], uint32_t a) {
    asm volatile("ldmatrix.sync.aligned.m8n8.x4.trans.shared.b16 {%0,%1,%2,%3}, [%4];" : "=r"(r[0]), "=r"(r[1]), "=r"(r[2]), "=r"(r[3]) : "r"(a) : "memory");
}
__device__ __forceinline__ void mma(float (&c)[4], const uint32_t (&a)[4], uint32_t b0, uint32_t b1) {
    asm volatile("mma.sync.aligned.m16n8k16.row.col.f32.bf16.bf16.f32 {%0,%1,%2,%3}, {%4,%5,%6,%7}, {%8,%9}, {%0,%1,%2,%3};"
                 : "+f"(c[0]), "+f"(c[1]), "+f"(c[2]), "+f"(c[3]) : "r"(a[0]), "r"(a[1]), "r"(a[2]), "r"(a[3]), "r"(b0), "r"(b1));
}
__device__ __forceinline__ uint32_t lds32(uint32_t a) { uint32_t v; asm volatile("ld.shared.b32 %0, [%1];" : "=r"(v) : "r"(a) : "memory"); return v; }
__device__ __forceinline__ uint32_t ldsv(uint32_t a) { uint32_t v; asm volatile("ld.volatile.shared.b32 %0, [%1];" : "=r"(v) : "r"(a) : "memory"); return v; }
__device__ __forceinline__ void stsv(uint32_t a, uint32_t v) { asm volatile("st.volatile.shared.b32 [%0], %1;" ::"r"(a), "r"(v) : "memory"); }
__device__ __forceinline__ float ldsf(uint32_t a) { float v; asm volatile("ld.shared.f32 %0, [%1];" : "=f"(v) : "r"(a) : "memory"); return v; }
__device__ __forceinline__ uint4 lds128(uint32_t a) { uint4 v; asm volatile("ld.shared.v4.b32 {%0,%1,%2,%3}, [%4];" : "=r"(v.x), "=r"(v.y), "=r"(v.z), "=r"(v.w) : "r"(a) : "memory"); return v; }
__device__ __forceinline__ void sts16(uint32_t a, uint16_t v) { asm volatile("st.shared.b16 [%0], %1;" ::"r"(a), "h"(v) : "memory"); }
__device__ __forceinline__ void sts32(uint32_t a, uint32_t v) { asm volatile("st.shared.b32 [%0], %1;" ::"r"(a), "r"(v) : "memory"); }
__device__ __forceinline__ void stsf2(uint32_t a, float x, float y) { asm volatile("st.shared.v2.f32 [%0], {%1,%2};" ::"r"(a), "f"(x), "f"(y) : "memory"); }
__device__ __forceinline__ void sts128(uint32_t a, uint4 v) { asm volatile("st.shared.v4.b32 [%0], {%1,%2,%3,%4};" ::"r"(a), "r"(v.x), "r"(v.y), "r"(v.z), "r"(v.w) : "memory"); }
__device__ __forceinline__ uint16_t f2bf(float x) { return __bfloat16_as_ushort(__float2bfloat16_rn(x)); }
__device__ __forceinline__ float bfround(float x) { return __bfloat162float(__float2bfloat16_rn(x)); }
__device__ __forceinline__ uint32_t pack2(float lo, float hi) { uint32_t r; asm("cvt.rn.bf16x2.f32 %0, %1, %2;" : "=r"(r) : "f"(hi), "f"(lo)); return r; }
__device__ __forceinline__ float ex2(float x) { float r; asm("ex2.approx.ftz.f32 %0, %1;" : "=f"(r) : "f"(x)); return r; }
__device__ __forceinline__ float lg2(float x) { float r; asm("lg2.approx.ftz.f32 %0, %1;" : "=f"(r) : "f"(x)); return r; }

__device__ __forceinline__ float rcp(float x) { float r; asm("rcp.approx.ftz.f32 %0, %1;" : "=f"(r) : "f"(x)); return r; }
__device__ __forceinline__ float merge2(float v0, float l0, float v1, float l1) {
    const float mx = fmaxf(l0, l1), e0 = ex2(l0 - mx), e1 = ex2(l1 - mx);
    return (e0 * v0 + e1 * v1) * rcp(e0 + e1);
}

__device__ __forceinline__ void sleep_ns(uint32_t ns) {
    uint32_t t0, t;
    asm volatile("mov.u32 %0, %clock;" : "=r"(t0));
    do { __nanosleep(200); asm volatile("mov.u32 %0, %clock;" : "=r"(t)); } while (t - t0 < 2 * ns);
}

__device__ __forceinline__ void ll_store2(ulonglong2* p, float a, float b, uint32_t tag) {
    unsigned long long x = ((unsigned long long)tag << 32) | __float_as_uint(a);
    unsigned long long y = ((unsigned long long)tag << 32) | __float_as_uint(b);
    asm volatile("st.relaxed.gpu.global.v2.b64 [%0], {%1,%2};" ::"l"(p), "l"(x), "l"(y) : "memory");
}
__device__ __forceinline__ void ll_red2(ulonglong2* p, float a, float b, uint32_t tag) {
    unsigned long long x = ((unsigned long long)tag << 32) | __float_as_uint(a);
    unsigned long long y = ((unsigned long long)tag << 32) | __float_as_uint(b);
    asm volatile("red.relaxed.gpu.global.add.u64 [%0], %1;\nred.relaxed.gpu.global.add.u64 [%0+8], %2;" ::"l"(p), "l"(x), "l"(y) : "memory");
}
__device__ __forceinline__ void ll_ld2(const void* p, unsigned long long& x, unsigned long long& y) {
    asm volatile("ld.relaxed.gpu.global.v2.b64 {%0,%1}, [%2];" : "=l"(x), "=l"(y) : "l"(p) : "memory");
}
__device__ __forceinline__ void ll_gather4(const ulonglong2* p, uint32_t tag, float& r0, float& r1) {
    unsigned long long x[4], y[4]; uint32_t it = 0;
    while (true) {
        bool ok = true;
#pragma unroll
        for (int k = 0; k < 4; k++) ll_ld2(p + k * 128, x[k], y[k]);
#pragma unroll
        for (int k = 0; k < 4; k++) ok = ok && (uint32_t)(x[k] >> 32) == tag && (uint32_t)(y[k] >> 32) == tag;
        if (ok) break;
        if (++it > SPIN_MAX) __trap();
        __nanosleep(BACKOFF);
    }
    r0 = (__uint_as_float((uint32_t)x[0]) + __uint_as_float((uint32_t)x[1])) + (__uint_as_float((uint32_t)x[2]) + __uint_as_float((uint32_t)x[3]));
    r1 = (__uint_as_float((uint32_t)y[0]) + __uint_as_float((uint32_t)y[1])) + (__uint_as_float((uint32_t)y[2]) + __uint_as_float((uint32_t)y[3]));
}
__device__ __forceinline__ void cnt_rendezvous(unsigned* c, uint32_t target, int tsk) {
    TS(tsk);
    asm volatile("red.release.gpu.global.add.u32 [%0], 1;" ::"l"(c) : "memory");
    if (tsk == 18) TS(tsk + 1);
    uint32_t v, it = 0;
    while (true) {
        asm volatile("ld.acquire.gpu.global.u32 %0, [%1];" : "=r"(v) : "l"(c) : "memory");
        if ((int)(v - target) >= 0) break;
        if (++it > SPIN_MAX) __trap();
        __nanosleep(BACKOFF);
    }
    asm volatile("fence.proxy.async.global;" ::: "memory");
}

__device__ __forceinline__ void matvec_loadA(uint32_t (&a)[8][4], uint32_t tile, uint32_t bar, int w, int lane) {
    const int i = lane >> 3, rr = lane & 7, chunk = 2 * w + (i & 1);
    const uint32_t a0 = tile + (chunk >> 3) * 8192 + (rr + 8 * (i >> 1)) * 128 + (((chunk & 7) ^ rr) << 4);
#pragma unroll
    for (int hh = 0; hh < 2; hh++) {
        mbar_wait(bar + hh * 8, 0);
#pragma unroll
        for (int k = 0; k < 4; k++) ldsm4t(a[hh * 4 + k], a0 + hh * CH + k * 2048);
    }
}
__device__ __forceinline__ void matvec_mma(float (&c)[4], const uint32_t (&a)[8][4], uint32_t vec, int nvec, int lane) {
    const uint32_t va = vec + (lane & (nvec - 1)) * VROW + (lane >> 3) * 16;
    float d[4][4];
#pragma unroll
    for (int q = 0; q < 4; q++) {
        uint32_t b[4];
        ldsm4(b, va + q * 64);
        d[q][0] = d[q][1] = d[q][2] = d[q][3] = 0.f;
        mma(d[q], a[2 * q], b[0], b[1]);
        mma(d[q], a[2 * q + 1], b[2], b[3]);
    }
#pragma unroll
    for (int k = 0; k < 4; k++) c[k] = (d[0][k] + d[1][k]) + (d[2][k] + d[3][k]);
}
__device__ __forceinline__ void matvecT(float (&c)[4], uint32_t tile, uint32_t vec, int nvec, uint32_t bar, int w, int lane) {
    uint32_t a[8][4];
    matvec_loadA(a, tile, bar, w, lane);
    matvec_mma(c, a, vec, nvec, lane);
}
template <class T> __device__ __forceinline__ T* pin(T* p) { asm volatile("" : "+l"(p)); return p; }
__device__ __forceinline__ bool ll_ok(unsigned long long x, unsigned long long y, uint32_t tag) { return (uint32_t)(x >> 32) == tag && (uint32_t)(y >> 32) == tag; }
__device__ __forceinline__ void ll_reld2(const void* p, unsigned long long& x, unsigned long long& y, bool need) {
    asm volatile("{\n.reg .pred q;\nsetp.ne.u32 q, %3, 0;\n@q ld.relaxed.gpu.global.v2.b64 {%0,%1}, [%2];\n}" : "+l"(x), "+l"(y) : "l"(p), "r"((uint32_t)need) : "memory");
}

__global__ void __launch_bounds__(NTHREADS, 1)
fused_decode_kernel(const char* __restrict__ wqraw, const __grid_constant__ Maps maps, const char* __restrict__ Kc, const char* __restrict__ Vc,
                    const __nv_bfloat16* __restrict__ xA, const __nv_bfloat16* __restrict__ xB,
                    __nv_bfloat16* __restrict__ out, const uint32_t zero) {
    if (threadIdx.x - 32u < 64u) {
        const uint32_t r = threadIdx.x - 32u;
        const uint32_t off = ((blockIdx.x & 3) << 20) + ((blockIdx.x >> 2) << 8) + ((r >> 1) << 13) + ((r & 1) << 7);
        asm volatile("prefetch.global.L2 [%0];" ::"l"(wqraw + off) : "memory");
    }
    extern __shared__ char smem_raw[];
    const uint32_t sm = ((uint32_t)__cvta_generic_to_shared(smem_raw) + 1023u) & ~1023u;
    const uint32_t bars = sm + OFF_BAR;
    const int cta = blockIdx.x, h = cta >> 2, j = cta & 3;
    uint64_t pol = 0;
    if (threadIdx.x == 0) {
        TS(0);
        asm volatile("createpolicy.fractional.L2::evict_first.b64 %0, 1.0;" : "=l"(pol));
#pragma unroll
        for (int i = 0; i < WIN; i++) mbar_init(bars + (B_WQB + i) * 8, 1);
        asm volatile("fence.mbarrier_init.release.cluster;" ::: "memory");
#pragma unroll
        for (int i = 0; i < WIN; i++) {
            mbar_expect(bars + (B_WQB + i) * 8, CH);
            tma3d(sm + OFF_S0 + i * CH, &maps.wqB + (i >> 1), j * 128 + (i & 1) * 64, h * 2, bars + (B_WQB + i) * 8, pol);
        }
    }
    const int tid = threadIdx.x < 64 ? threadIdx.x + 384 : threadIdx.x - 64, warp = tid >> 5, lane = tid & 31;

    if (warp == 12) {
        const size_t kvoff = ((size_t)(((j >> 1) * 32 + h) * 4096 + (j & 1) * 2048)) * 256;
        const char* kp = Kc + kvoff;
        const char* vp = Vc + kvoff;
        __syncwarp();
        bar_arrive(0, NTHREADS);
        bar_sync(3, 64);
        if (lane == 0) {
            uint32_t pb[WHI];
#pragma unroll
            for (int i = 0; i < WHI; i++) pb[i] = i < WHI - WIN ? (bars + B_WO * 8) | 1u : bars + (B_WQB + i - (WHI - WIN)) * 8;
            auto pace = [&](uint32_t bar, uint32_t par, uint32_t wina) {
                uint32_t it = 0;
                while (true) {
                    const uint32_t win = ldsv(wina);
                    uint32_t busy = 0;
#pragma unroll
                    for (int i = 0; i < WHI; i++) busy += mbar_test(pb[i] & ~1u, pb[i] & 1u) ^ 1u;
                    if (busy < win) break;
                    if (++it > SPIN_MAX) __trap();
                }
#pragma unroll
                for (int i = 0; i + 1 < WHI; i++) pb[i] = pb[i + 1];
                pb[WHI - 1] = bar | par;
            };
            auto side = [&](const CUtensorMap* m, uint32_t dst, int bidx, int c1, int c2, uint32_t wina) {
                const uint32_t bar = bars + bidx * 8;
                pace(bar, 0, wina);
                mbar_expect(bar, CH);
                tma3d(dst, m, c1, c2, bar, pol);
            };
#pragma unroll 1
            for (int i = WIN; i < 6; i++)
                side(&maps.wqB + (i >> 1), sm + OFF_S0 + i * CH, B_WQB + i, j * 128 + (i & 1) * 64, h * 2, sm + OFF_WIN);
            TS(1);
            uint32_t slot = 0, use = 0;
            int nuv = 0;
#pragma unroll 1
            for (int n = 0; n < 2 * NTILE; n++) {
                if (n == RING) {
                    mbar_wait(bars + B_FREE * 8, 0);
#pragma unroll 1
                    for (int q = 0; q < 4; q++) side(&maps.ckv, sm + OFF_S0 + q * CH, B_CKV + q, cta * 64 + q * 16, 0, sm + OFF_WIN);
                }
                if (nuv < 2 && n > RING && (n >= 2 * NTILE - 8 || mbar_test(bars + B_FREE * 8, 1))) {
                    mbar_wait(bars + B_FREE * 8, 1);
                    side(&maps.wuv, sm + OFF_S1 + nuv * CH, B_WUV + nuv, j * 128 + nuv * 64, h * 2, sm + OFF_WIN);
                    nuv++;
                }
                const uint32_t fb = bars + slot * 8;
                pace(fb, use & 1, sm + OFF_WIN);
                mbar_wait(fb + B_EMPTY * 8, (use & 1) ^ 1);
                mbar_expect(fb, CH);
                bulk1d(sm + OFF_RING + slot * CH, ((n & 1) ? vp : kp) + (size_t)(n >> 1) * CH, fb, pol);
                asm volatile("red.relaxed.gpu.global.add.u32 [%0], 1;" ::"l"(&g_cnt[64]) : "memory");
                stsv(sm + OFF_NOW, n + 1);
                if (++slot == RING) { slot = 0; use++; }
            }
            TS(2);
            mbar_wait(bars + B_FREE * 8, 0);
#pragma unroll 1
            for (int i = 0; i < 4; i++) {
                const uint32_t bar = bars + (B_WO + 2 * i) * 8;
                pace(bar + 8, 0, sm + OFF_TWIN);
#pragma unroll
                for (int k = 0; k < 2; k++) {
                    mbar_expect(bar + k * 8, CH / 2);
                    tma3d(sm + OFF_S0 + i * CH + k * (CH / 2), &maps.woA + (i >> 1), h * 128 + (i & 1) * 64, j * 2 + k, bar + k * 8, pol);
                }
            }
            TS(3);
        }
    } else if (warp == 13) {
        if (lane == 0) {
#pragma unroll
            for (int i = 0; i < NBAR; i++)
                if (i < B_WQB || i >= B_WQB + WIN)
                    mbar_init(bars + i * 8, i == B_FREE ? 8 : (i >= B_EMPTY && i < B_EMPTY + RING) ? 4 : 1);
            asm volatile("fence.mbarrier_init.release.cluster;" ::: "memory");
#pragma unroll
            for (int i = 2; i < 8; i++) asm volatile("prefetch.tensormap [%0];" ::"l"(&maps.wqB + i) : "memory");
            stsv(sm + OFF_NOW, 0); stsv(sm + OFF_WIN, WIN); stsv(sm + OFF_TWIN, PREWIN);
        }
        __syncwarp();
        bar_arrive(3, 64);
        bar_sync(0, NTHREADS);
        if (lane == 0) {
            const uint32_t base = (lds32(sm + OFF_TAG) - 1u) * (NCTA * 2 * NTILE);
            mbar_wait(bars + (B_WUK + 1) * 8, 0);
            uint32_t it = 0;
            while (true) {
                const uint32_t n = ldsv(sm + OFF_NOW);
                uint32_t v;
                asm volatile("ld.relaxed.gpu.global.u32 %0, [%1];" : "=r"(v) : "l"(&g_cnt[64]) : "memory");
                v -= base;
                if (v >= NCTA * 2 * NTILE - GATE_W) break;
                const int diff = (int)(n * NCTA) - (int)v;
                stsv(sm + OFF_WIN, diff < -THETA ? WHI : WIN - (diff > THETA) - (v >= NCTA * END_V));
                if (++it > SPIN_MAX) __trap();
                __nanosleep(BACKOFF2);
            }
            stsv(sm + OFF_WIN, WHI); stsv(sm + OFF_TWIN, TAILWIN);
            TS(24);
        }
    } else if (warp < 4) {
        const int g = lane >> 2, t = lane & 3, i = lane >> 3, rr = lane & 7;
        if (tid == 0) {
            const unsigned e = atomicAdd(&g_epoch, 1u);
            sts32(sm + OFF_TAG, (e >> 7) + 1u);
        }
        bar_sync(0, NTHREADS);
        const uint32_t tag = lds32(sm + OFF_TAG);
        {
            mbar_wait(bars + 8, 0);
            float q0, q1;
            ll_gather4(&g_e1[0][h * 4][tid], tag, q0, q1);
            sts16(sm + OFF_QB + tid * 2, f2bf((j >> 1) ? q1 : q0));
        }
        bar_sync(1, 128);
        if (tid == 0) TS(4);
        uint32_t qf[8][2];
#pragma unroll
        for (int c = 0; c < 8; c++) {
            const uint32_t a = sm + OFF_QB + (((c + g) & 7) * 8 + 2 * t) * 2;
            qf[c][0] = lds32(a); qf[c][1] = lds32(a + 128);
        }
        float acc[8][4];
#pragma unroll
        for (int c = 0; c < 8; c++) { acc[c][0] = acc[c][1] = acc[c][2] = acc[c][3] = 0.f; }
        float m = -INFINITY, l = 0.f;
        const bool diag = (t == (g >> 1));
        const uint32_t krow = sm + OFF_RING + (warp * 16 + rr + 8 * (i & 1)) * 256 + (i >> 1) * 128;
        const uint32_t vrow = sm + OFF_RING + (warp * 16 + rr + 8 * (i >> 1)) * 256 + (i & 1) * 128;
        uint32_t slot = 0, ph = 0;
        ulonglong2* const e5own = pin(&g_e5[cta][tid]);
        uint32_t a[8][4], b0, b1;
#pragma unroll 1
        for (int tile = 0;; tile++) {
            if (tile == NTILE - 8) ll_store2(e5own, 0.f, 0.f, 0u);
            mbar_wait(bars + slot * 8, ph);
#pragma unroll
            for (int c = 0; c < 8; c++) ldsm4(a[c], krow + slot * CH + (((c + rr) & 7) << 4));
            __syncwarp();
            if (lane == 0) mbar_arrive(bars + (B_EMPTY + slot) * 8 + ((a[0][0] | a[1][0] | a[2][0] | a[3][0] | a[4][0] | a[5][0] | a[6][0] | a[7][0]) & zero));
            if (++slot == RING) { slot = 0; ph ^= 1; }
            float s0[4] = {0.f, 0.f, 0.f, 0.f}, s1[4] = {0.f, 0.f, 0.f, 0.f};
#pragma unroll
            for (int c = 0; c < 8; c += 2) { mma(s0, a[c], qf[c][0], qf[c][1]); mma(s1, a[c + 1], qf[c + 1][0], qf[c + 1][1]); }
            float slo = (g & 1) ? s0[1] + s1[1] : s0[0] + s1[0];
            float shi = (g & 1) ? s0[3] + s1[3] : s0[2] + s1[2];
            slo = diag ? bfround(bfround(slo) * SCALE) : -INFINITY;
            shi = diag ? bfround(bfround(shi) * SCALE) : -INFINITY;
            int key = __float_as_int(fmaxf(slo, shi));
            key ^= (key >> 31) & 0x7fffffff;
            key = __reduce_max_sync(0xffffffffu, key);
            key ^= (key >> 31) & 0x7fffffff;
            const float mn = fmaxf(m, __int_as_float(key));
            const float alpha = ex2((m - mn) * LOG2E);
            m = mn;
            const float plo = ex2((slo - mn) * LOG2E), phi = ex2((shi - mn) * LOG2E);
            l = l * alpha + (plo + phi);
            b0 = (g & 1) ? pack2(0.f, plo) : pack2(plo, 0.f);
            b1 = (g & 1) ? pack2(0.f, phi) : pack2(phi, 0.f);
#pragma unroll
            for (int c = 0; c < 8; c++) { acc[c][0] *= alpha; acc[c][1] *= alpha; acc[c][2] *= alpha; acc[c][3] *= alpha; }
            if (tile == NTILE - 1) break;
            mbar_wait(bars + slot * 8, ph);
#pragma unroll
            for (int c = 0; c < 8; c++) ldsm4t(a[c], vrow + slot * CH + (((c + rr) & 7) << 4));
            __syncwarp();
            if (lane == 0) mbar_arrive(bars + (B_EMPTY + slot) * 8 + ((a[0][0] | a[1][0] | a[2][0] | a[3][0] | a[4][0] | a[5][0] | a[6][0] | a[7][0]) & zero));
            if (++slot == RING) { slot = 0; ph ^= 1; }
#pragma unroll
            for (int c = 0; c < 8; c++) mma(acc[c], a[c], b0, b1);
        }
        const ulonglong2* ps = e5own + ((j ^ 1) - j) * 128;
        const ulonglong2* po = e5own + (((j & 2) ^ 2) - j) * 128;
        unsigned long long x[3], y[3];
        ll_ld2(ps, x[0], y[0]); ll_ld2(po, x[1], y[1]); ll_ld2(po + 128, x[2], y[2]);
#pragma unroll
        for (int o = 16; o; o >>= 1) l += __shfl_xor_sync(0xffffffffu, l, o);
        if (lane == 0) stsf2(sm + OFF_ML + warp * 8, m, l);
        mbar_wait(bars + B_S2 * 8, 0);
        bar_sync(1, 128);
        float lse, oval;
        {
            const uint4 ml0 = lds128(sm + OFF_ML), ml1 = lds128(sm + OFF_ML + 16);
            const float m0 = __uint_as_float(ml0.x), m1 = __uint_as_float(ml0.z), m2 = __uint_as_float(ml1.x), m3 = __uint_as_float(ml1.z);
            const float M = fmaxf(fmaxf(m0, m1), fmaxf(m2, m3));
            const float L = (ex2((m0 - M) * LOG2E) * __uint_as_float(ml0.y) + ex2((m1 - M) * LOG2E) * __uint_as_float(ml0.w))
                          + (ex2((m2 - M) * LOG2E) * __uint_as_float(ml1.y) + ex2((m3 - M) * LOG2E) * __uint_as_float(ml1.w));
            const float f = ex2((m - M) * LOG2E) * rcp(L);
            lse = M * LOG2E + lg2(L);
            mbar_wait(bars + slot * 8, ph);
#pragma unroll
            for (int c = 0; c < 8; c++) ldsm4t(a[c], vrow + slot * CH + (((c + rr) & 7) << 4));
#pragma unroll
            for (int c = 0; c < 8; c++) mma(acc[c], a[c], b0, b1);
            if (tid == 0) TS(5);
            float v[2][8];
#pragma unroll
            for (int c = 0; c < 8; c++) { v[0][c] = acc[c][0] + acc[(c + 7) & 7][1]; v[1][c] = acc[c][2] + acc[(c + 7) & 7][3]; }
#pragma unroll
            for (int c = 0; c < 4; c++) { v[0][c] += __shfl_xor_sync(0xffffffffu, v[0][c + 4], 2); v[1][c] += __shfl_xor_sync(0xffffffffu, v[1][c + 4], 2); }
            const int src = (lane & ~3) | ((lane + 3) & 3);
#pragma unroll
            for (int c = 0; c < 2; c++) { v[0][c] += __shfl_sync(0xffffffffu, v[0][c + 2], src); v[1][c] += __shfl_sync(0xffffffffu, v[1][c + 2], src); }
            uint4 u;
            u.x = __float_as_uint(v[0][0] * f); u.y = __float_as_uint(v[0][1] * f); u.z = __float_as_uint(v[1][0] * f); u.w = __float_as_uint(v[1][1] * f);
            sts128(sm + OFF_S2 + tid * 16, u);
            bar_sync(1, 128);
            const uint32_t ra = sm + OFF_S2 + tid * 4;
            oval = (ldsf(ra) + ldsf(ra + 512)) + (ldsf(ra + 1024) + ldsf(ra + 1536));
            ll_red2(e5own, oval, lse, tag);
        }
        if (tid == 0) TS(6);
        {
            uint32_t it = 0;
            while (true) {
                const bool n0 = !ll_ok(x[0], y[0], tag), n1 = !ll_ok(x[1], y[1], tag), n2 = !ll_ok(x[2], y[2], tag);
                if (!__any_sync(0xffffffffu, n0 | n1 | n2)) break;
                ll_reld2(ps, x[0], y[0], n0); ll_reld2(po, x[1], y[1], n1); ll_reld2(po + 128, x[2], y[2], n2);
                if (++it > SPIN_MAX) __trap();
            }
            const float sv = __uint_as_float((uint32_t)x[0]), sl = __uint_as_float((uint32_t)y[0]);
            const float oa = merge2((j & 1) ? sv : oval, (j & 1) ? sl : lse, (j & 1) ? oval : sv, (j & 1) ? lse : sl);
            const float ob = merge2(__uint_as_float((uint32_t)x[1]), __uint_as_float((uint32_t)y[1]), __uint_as_float((uint32_t)x[2]), __uint_as_float((uint32_t)y[2]));
            const uint32_t oa_ = sm + OFF_OB + ((tid & 2) * 32 + ((tid >> 2 & 3) * 2 + (tid & 1)) * 8 + (tid >> 4)) * 2;
            sts16(oa_ + (j >> 1) * VROW, f2bf(oa)); sts16(oa_ + ((j >> 1) ^ 1) * VROW, f2bf(ob));
        }
        bar_arrive(4, 256 + 128);
        if (tid == 0) TS(16);
    } else {
        const int st = tid - 128, w = warp - 4;
        const int g = lane >> 2, t = lane & 3, i = lane >> 3, rr = lane & 7;
        if (t == 0) {
#pragma unroll
            for (int k = 0; k < 4; k++) ll_store2(&g_e1[k >> 1][cta][w * 16 + g + (k & 1) * 8], 0.f, 0.f, 0u);
        }
        if (st < 64) {
            const int which = st >> 5, b = (st >> 4) & 1, c = st & 15;
            const uint4 v = __ldg((const uint4*)((which ? xA : xB) + b * 512 + j * 128) + c);
            sts128(sm + OFF_XB + (which * 2 + b) * VROW + c * 16, v);
        }
        bar_sync(0, NTHREADS);
        const uint32_t tag = lds32(sm + OFF_TAG);
        float c[4];
#pragma unroll 1
        for (int which = 0; which < 2; which++) {
            matvecT(c, sm + OFF_S0 + which * 2 * CH, sm + OFF_XB + which * 2 * VROW, 2, bars + (B_WQB + which * 2) * 8, w, lane);
            if (t == 0) {
                ll_store2(&g_e1[which][cta][w * 16 + g], c[0], c[1], tag);
                ll_store2(&g_e1[which][cta][w * 16 + g + 8], c[2], c[3], tag);
            }
        }
        __syncwarp();
        if (lane == 0) mbar_arrive(bars + B_FREE * 8);
        if (st == 0) TS(8);
        if (st < 128) {
            float q0, q1;
            sleep_ns(POLL_DELAY);
            ll_gather4(&g_e1[1][h * 4][st], tag, q0, q1);
            sts16(sm + OFF_QA + st * 2, f2bf(q0)); sts16(sm + OFF_QA + VROW + st * 2, f2bf(q1));
        }
        bar_sync(2, 256);
        if (st == 0) TS(9);
        {
            const int row = w * 16 + rr + 8 * (i & 1);
            const uint32_t a0 = sm + OFF_S2 + (row >> 6) * CH + (row & 63) * 128;
            const uint32_t va = sm + OFF_QA + g * VROW + t * 4;
            float d[4] = {0.f, 0.f, 0.f, 0.f};
            c[0] = c[1] = c[2] = c[3] = 0.f;
            mbar_wait(bars + (B_WUK + (w >> 2)) * 8, 0);
#pragma unroll
            for (int ks = 0; ks < 8; ks++) {
                const int chunk = 2 * ks + (i >> 1);
                uint32_t a[4];
                ldsm4(a, a0 + (chunk >> 3) * 8192 + (((chunk & 7) ^ rr) << 4));
                const uint32_t b0 = (g < 2) ? lds32(va + ks * 32) : 0u, b1 = (g < 2) ? lds32(va + ks * 32 + 16) : 0u;
                if (ks & 1) mma(d, a, b0, b1); else mma(c, a, b0, b1);
            }
            if (t == 0) {
                const uint32_t qs = sm + OFF_QS + (w * 16 + g) * 2;
                sts16(qs, f2bf(c[0] + d[0])); sts16(qs + VROW, f2bf(c[1] + d[1]));
                sts16(qs + 16, f2bf(c[2] + d[2])); sts16(qs + VROW + 16, f2bf(c[3] + d[3]));
            }
            bar_sync(2, 256);
            if (w == 0) {
                const int b = lane >> 4, cc = lane & 15;
                g_qabs[(b * 32 + h) * 64 + ((j * 16 + cc) ^ (h & 7))] = lds128(sm + OFF_QS + b * VROW + cc * 16);
                __syncwarp();
                if (lane == 0) {
                    cnt_rendezvous(&g_cnt[0], tag * 128u, 18);
                    TS(10);
                    mbar_expect(bars + B_GATH * 8, 2 * CH);
                    bulk1d_n(sm + OFF_S2, g_qabs + (cta >> 6) * 2048, 2 * CH, bars + B_GATH * 8);
                }
                __syncwarp();
            }
        }
        mbar_wait(bars + B_GATH * 8, 0);
        if (st == 0) TS(11);
        {
            const int mt = w & 1, kg = w >> 1;
            const uint32_t qa = sm + OFF_S2 + (mt * 16 + rr + 8 * (i & 1)) * 1024;
            const uint32_t ka = sm + OFF_S0 + kg * CH + (rr + 8 * (i >> 1)) * 128;
            float s0[4] = {0.f, 0.f, 0.f, 0.f}, s1[4] = {0.f, 0.f, 0.f, 0.f};
            mbar_wait(bars + (B_CKV + kg) * 8, 0);
#pragma unroll 2
            for (int gq = 0; gq < 8; gq++) {
#pragma unroll
                for (int k4 = 0; k4 < 4; k4++) {
                    uint32_t a[4], b[4];
                    ldsm4(a, qa + gq * 128 + (((2 * k4 + (i >> 1)) ^ rr) << 4));
                    ldsm4(b, ka + gq * 2048 + (((2 * k4 + (i & 1)) ^ rr) << 4));
                    mma(s0, a, b[0], b[1]);
                    mma(s1, a, b[2], b[3]);
                }
            }
            const uint32_t sa = sm + OFF_SC + ((mt * 16 + g) * 68 + kg * 16 + 2 * t) * 4;
            stsf2(sa, s0[0], s0[1]); stsf2(sa + 32, s1[0], s1[1]);
            stsf2(sa + 8 * 68 * 4, s0[2], s0[3]); stsf2(sa + 8 * 68 * 4 + 32, s1[2], s1[3]);
        }
        bar_sync(2, 256);
        {
            const int head = w * 4 + i;
            const uint32_t sa = sm + OFF_SC + (head * 68 + rr * 8) * 4;
            const uint4 u0 = lds128(sa), u1 = lds128(sa + 16);
            float s[8] = {__uint_as_float(u0.x), __uint_as_float(u0.y), __uint_as_float(u0.z), __uint_as_float(u0.w),
                          __uint_as_float(u1.x), __uint_as_float(u1.y), __uint_as_float(u1.z), __uint_as_float(u1.w)};
            float mx = s[0];
#pragma unroll
            for (int k = 1; k < 8; k++) mx = fmaxf(mx, s[k]);
#pragma unroll
            for (int o = 1; o < 8; o <<= 1) mx = fmaxf(mx, __shfl_xor_sync(0xffffffffu, mx, o));
            float sum = 0.f;
#pragma unroll
            for (int k = 0; k < 8; k++) { s[k] = ex2((s[k] - mx) * (SCALE * LOG2E)); sum += s[k]; }
#pragma unroll
            for (int o = 1; o < 8; o <<= 1) sum += __shfl_xor_sync(0xffffffffu, sum, o);
            const float inv = __fdividef(1.f, sum);
            uint4 p;
            p.x = pack2(s[0] * inv, s[1] * inv); p.y = pack2(s[2] * inv, s[3] * inv);
            p.z = pack2(s[4] * inv, s[5] * inv); p.w = pack2(s[6] * inv, s[7] * inv);
            sts128(sm + OFF_P + head * 128 + ((rr ^ (head & 7)) << 4), p);
            if (rr == 0) ((float*)g_lse)[head * 128 + cta] = mx * (SCALE * LOG2E) + lg2(sum);
        }
        bar_sync(2, 256);
        {
            float o[2][8][4];
#pragma unroll
            for (int mt = 0; mt < 2; mt++)
#pragma unroll
                for (int n = 0; n < 8; n++) { o[mt][n][0] = o[mt][n][1] = o[mt][n][2] = o[mt][n][3] = 0.f; }
            const uint32_t pa = sm + OFF_P + (rr + 8 * (i & 1)) * 128;
            const uint32_t va = sm + OFF_S0 + w * 2048 + (rr + 8 * (i & 1)) * 128;
#pragma unroll 1
            for (int kq = 0; kq < 4; kq++) {
                uint32_t a0[4], a1[4];
                ldsm4(a0, pa + (((2 * kq + (i >> 1)) ^ rr) << 4));
                ldsm4(a1, pa + 2048 + (((2 * kq + (i >> 1)) ^ rr) << 4));
#pragma unroll
                for (int n = 0; n < 8; n += 2) {
                    uint32_t b[4];
                    ldsm4t(b, va + kq * CH + (((n + (i >> 1)) ^ rr) << 4));
                    mma(o[0][n], a0, b[0], b[1]); mma(o[1][n], a1, b[0], b[1]);
                    mma(o[0][n + 1], a0, b[2], b[3]); mma(o[1][n + 1], a1, b[2], b[3]);
                }
            }
#pragma unroll
            for (int mt = 0; mt < 2; mt++)
#pragma unroll
                for (int hf = 0; hf < 2; hf++) {
                    const uint32_t dst = sm + OFF_S2 + (mt * 16 + hf * 8 + g) * 1024 + w * 128 + t * 16;
#pragma unroll
                    for (int nb = 0; nb < 2; nb++) {
                        uint4 v;
                        v.x = pack2(o[mt][nb * 4 + 0][hf * 2], o[mt][nb * 4 + 0][hf * 2 + 1]);
                        v.y = pack2(o[mt][nb * 4 + 1][hf * 2], o[mt][nb * 4 + 1][hf * 2 + 1]);
                        v.z = pack2(o[mt][nb * 4 + 2][hf * 2], o[mt][nb * 4 + 2][hf * 2 + 1]);
                        v.w = pack2(o[mt][nb * 4 + 3][hf * 2], o[mt][nb * 4 + 3][hf * 2 + 1]);
                        sts128(dst + nb * 64, v);
                    }
                }
            asm volatile("fence.proxy.async.shared::cta;" ::: "memory");
            __syncwarp();
            if (lane == 0) mbar_arrive(bars + B_FREE * 8);
            if (t == 0) { ll_store2(&g_e4[cta][w * 16 + g], 0.f, 0.f, 0u); ll_store2(&g_e4[cta][w * 16 + g + 8], 0.f, 0.f, 0u); }
            if (st < 8) g_acc[cta][st] = make_float4(0.f, 0.f, 0.f, 0.f);
        }
        bar_sync(2, 256);
        if (st == 0) {
            TS(12);
#pragma unroll 1
            for (int k = 0; k < ST_SPLIT; k++) {
                asm volatile("cp.async.bulk.tensor.3d.global.shared::cta.bulk_group [%0, {%2,%3,%4}], [%1];"
                             ::"l"(&maps.ctxp), "r"(sm + OFF_S2 + k * (2 * CH / ST_SPLIT)), "r"(0), "r"(cta), "r"(k * (128 / ST_SPLIT)) : "memory");
                if (k + 1 < ST_SPLIT) __nanosleep(ST_GAP);
            }
            asm volatile("cp.async.bulk.commit_group;" ::: "memory");
            asm volatile("cp.async.bulk.wait_group 0;" ::: "memory");
            cnt_rendezvous(&g_cnt[32], tag * 128u, 20);
            TS(13);
            mbar_expect(bars + B_GATH * 8, 2 * CH + 512);
            bulk1d_n(sm + OFF_LSE, g_lse + h * 32, 512, bars + B_GATH * 8);
            bulk1d_n(sm + OFF_S2, g_ctxp + cta * 2048, 2 * CH, bars + B_GATH * 8);
        }
        __syncwarp();
        {
            mbar_wait(bars + B_GATH * 8, 1);
            if (st == 0) TS(22);
            uint4 v[8];
#pragma unroll
            for (int k = 0; k < 8; k++) v[k] = lds128(sm + OFF_S2 + (k * 256 + st) * 16);
            float ls[4];
#pragma unroll
            for (int k = 0; k < 4; k++) ls[k] = ldsf(sm + OFF_LSE + (k * 32 + lane) * 4);
            float m0 = fmaxf(ls[0], ls[1]), m1 = fmaxf(ls[2], ls[3]);
#pragma unroll
            for (int o = 16; o; o >>= 1) { m0 = fmaxf(m0, __shfl_xor_sync(0xffffffffu, m0, o)); m1 = fmaxf(m1, __shfl_xor_sync(0xffffffffu, m1, o)); }
            ls[0] = ex2(ls[0] - m0); ls[1] = ex2(ls[1] - m0); ls[2] = ex2(ls[2] - m1); ls[3] = ex2(ls[3] - m1);
            float z0 = ls[0] + ls[1], z1 = ls[2] + ls[3];
#pragma unroll
            for (int o = 16; o; o >>= 1) { z0 += __shfl_xor_sync(0xffffffffu, z0, o); z1 += __shfl_xor_sync(0xffffffffu, z1, o); }
            z0 = __fdividef(1.f, z0); z1 = __fdividef(1.f, z1);
            ls[0] *= z0; ls[1] *= z0; ls[2] *= z1; ls[3] *= z1;
            float a[2][8];
#pragma unroll
            for (int e = 0; e < 8; e++) a[0][e] = a[1][e] = 0.f;
            const int rg = st >> 4;
#pragma unroll
            for (int k = 0; k < 8; k++) {
                const float wt = __shfl_sync(0xffffffffu, ls[k >> 1], rg + 16 * (k & 1));
                const uint32_t u[4] = {v[k].x, v[k].y, v[k].z, v[k].w};
#pragma unroll
                for (int e = 0; e < 4; e++) {
                    a[k >> 2][2 * e] += wt * __uint_as_float(u[e] << 16);
                    a[k >> 2][2 * e + 1] += wt * __uint_as_float(u[e] & 0xffff0000u);
                }
            }
            const int b = lane >> 4, u16 = lane & 15;
            const uint32_t ra = sm + OFF_SC + (w * 256 + b * 128 + (u16 >> 3) * 64 + ((u16 >> 2) & 1) * 32 + (u16 & 3) * 2) * 4;
#pragma unroll
            for (int e = 0; e < 8; e += 2) {
                const float k0 = b ? a[1][e] : a[0][e], k1 = b ? a[1][e + 1] : a[0][e + 1];
                const float s0 = b ? a[0][e] : a[1][e], s1 = b ? a[0][e + 1] : a[1][e + 1];
                stsf2(ra + (e >> 1) * 32, k0 + __shfl_xor_sync(0xffffffffu, s0, 16), k1 + __shfl_xor_sync(0xffffffffu, s1, 16));
            }
            bar_sync(2, 256);
            if (st == 0) mbar_arrive(bars + B_S2 * 8);
            float s = 0.f;
#pragma unroll
            for (int k = 0; k < 8; k++) s += ldsf(sm + OFF_SC + (k * 256 + st) * 4);
            const float hi = bfround(s);
            const uint32_t ca = sm + OFF_CC + (st >> 7) * VROW + (st & 127) * 2;
            sts16(ca, f2bf(hi)); sts16(ca + 2 * VROW, f2bf(s - hi));
            bar_sync(2, 256);
        }
        matvecT(c, sm + OFF_S1, sm + OFF_CC, 4, bars + B_WUV * 8, w, lane);
#pragma unroll
        for (int k = 0; k < 4; k++) c[k] += __shfl_down_sync(0xffffffffu, c[k], 1);
        if (t == 0) {
            ll_store2(&g_e4[cta][w * 16 + g], c[0], c[1], tag);
            ll_store2(&g_e4[cta][w * 16 + g + 8], c[2], c[3], tag);
        }
        __syncwarp();
        if (lane == 0) mbar_arrive(bars + B_FREE * 8);
        if (st == 0) TS(23);
        if (st < 128) {
            float q0, q1;
            sleep_ns(POLL_DELAY2);
            ll_gather4(&g_e4[h * 4][st], tag, q0, q1);
            sts16(sm + OFF_CA + st * 2, f2bf(q0)); sts16(sm + OFF_CA + VROW + st * 2, f2bf(q1));
        }
        if (st == 0) TS(14);
        bar_sync(2, 256);
        {
            const int chunk = 2 * w + (i & 1);
            const uint32_t a0 = sm + OFF_S0 + (chunk >> 3) * 8192 + (rr + 8 * (i >> 1)) * 128 + (((chunk & 7) ^ rr) << 4);
            const uint32_t va = sm + OFF_CA + (lane & 1) * VROW + i * 16;
            const uint32_t wb = bars + (B_WO + (w >> 2)) * 8;
            float4* const accp = pin(&g_acc[j * 32 + (st >> 3)][st & 7]);
            __nv_bfloat16* const outp = pin(out + (t >> 1) * 512 + j * 128 + w * 16 + (t & 1) * 8 + g);
            float y0 = 0.f, y1 = 0.f;
            int tp = t;
            asm volatile("" : "+r"(tp));
#pragma unroll
            for (int ab = 0; ab < 2; ab++) {
                uint32_t a[4][4], b[4][4];
                float d[4][4];
                mbar_wait(wb + ab * 32, 0);
#pragma unroll
                for (int k = 0; k < 4; k++) ldsm4t(a[k], a0 + ab * 2 * CH + k * 2048);
                if (ab) bar_sync(4, 256 + 128);
#pragma unroll
                for (int q = 0; q < 4; q++) ldsm4(b[q], va + ab * 2 * VROW + q * 64);
#pragma unroll
                for (int k = 0; k < 4; k++) {
                    d[k][0] = d[k][1] = d[k][2] = d[k][3] = 0.f;
                    mma(d[k], a[k], b[k >> 1][(k & 1) * 2], b[k >> 1][(k & 1) * 2 + 1]);
                }
                mbar_wait(wb + ab * 32 + 16, 0);
                if (st == 0) TS(25 + ab);
#pragma unroll
                for (int k = 0; k < 4; k++) ldsm4t(a[k], a0 + ab * 2 * CH + CH + k * 2048);
#pragma unroll
                for (int k = 0; k < 4; k++) mma(d[k], a[k], b[2 + (k >> 1)][(k & 1) * 2], b[2 + (k >> 1)][(k & 1) * 2 + 1]);
                float z[4];
#pragma unroll
                for (int k = 0; k < 4; k++) z[k] = (d[0][k] + d[1][k]) + (d[2][k] + d[3][k]);
                y0 = tp == 2 * ab ? z[0] : tp == 2 * ab + 1 ? z[2] : y0;
                y1 = tp == 2 * ab ? z[1] : tp == 2 * ab + 1 ? z[3] : y1;
                if (st == 0) TS(15 + 2 * ab);
            }
            float o0, o1, n0, n1;
            asm volatile("atom.relaxed.gpu.global.add.v4.f32 {%0,%2,%1,%3}, [%4], {%5,%7,%6,%7};"
                         : "=f"(o0), "=f"(o1), "=f"(n0), "=f"(n1) : "l"(accp), "f"(y0), "f"(y1), "f"(1.f) : "memory");
            asm volatile("{\n.reg .pred p, q;\n.reg .b16 lo, hi;\nsetp.eq.f32 p, %2, 0f41F80000;\nsetp.eq.f32 q, %3, 0f41F80000;\n"
                         "mov.b32 {lo, hi}, %1;\n@p st.global.b16 [%0], lo;\n@q st.global.b16 [%0 + 2048], hi;\n}"
                         ::"l"(outp), "r"(pack2(o0 + y0, o1 + y1)), "f"(n0), "f"(n1) : "memory");
        }
    }
}

typedef CUresult (*EncodeFn)(CUtensorMap*, CUtensorMapDataType, cuuint32_t, void*, const cuuint64_t*, const cuuint64_t*,
                             const cuuint32_t*, const cuuint32_t*, CUtensorMapInterleave, CUtensorMapSwizzle,
                             CUtensorMapL2promotion, CUtensorMapFloatOOBfill);

void make_map(EncodeFn enc, CUtensorMap* m, void* p, unsigned rows, unsigned cols, unsigned br, unsigned bg) {
    cuuint64_t gd[3] = {64, rows, cols / 64};
    cuuint64_t gs[2] = {(cuuint64_t)cols * 2, 128};
    cuuint32_t bx[3] = {64, br, bg};
    cuuint32_t es[3] = {1, 1, 1};
    enc(m, CU_TENSOR_MAP_DATA_TYPE_BFLOAT16, 3, p, gd, gs, bx, es, CU_TENSOR_MAP_INTERLEAVE_NONE,
        CU_TENSOR_MAP_SWIZZLE_128B, CU_TENSOR_MAP_L2_PROMOTION_L2_128B, CU_TENSOR_MAP_FLOAT_OOB_FILL_NONE);
}

}

extern "C" void kernel_launch(void* const* d_in, const int* in_sizes, int n_in, void* d_out, int out_size) {
    static EncodeFn enc = nullptr;
    if (!enc) {
        void* fn = nullptr;
        cudaDriverEntryPointQueryResult qr;
        cudaGetDriverEntryPoint("cuTensorMapEncodeTiled", &fn, cudaEnableDefault, &qr);
        enc = (EncodeFn)fn;
        cudaFuncSetAttribute(fused_decode_kernel, cudaFuncAttributeMaxDynamicSharedMemorySize, SMEM_BYTES);
    }
    Maps maps;
    make_map(enc, &maps.wqB, d_in[9], 512, 4096, 64, 2);
    make_map(enc, &maps.wqA, d_in[2], 512, 4096, 64, 2);
    make_map(enc, &maps.wuk, d_in[3], 512, 4096, 64, 2);
    make_map(enc, &maps.wuv, d_in[4], 512, 4096, 64, 2);
    make_map(enc, &maps.woA, d_in[5], 4096, 512, 64, 1);
    make_map(enc, &maps.woB, d_in[10], 4096, 512, 64, 1);
    make_map(enc, &maps.ckv, d_in[1], 8192, 512, 16, 8);
    {
        void* p = nullptr;
        cudaGetSymbolAddress(&p, g_ctxp);
        cuuint64_t gd[3] = {128, 128, 128};
        cuuint64_t gs[2] = {256, 32768};
        cuuint32_t bx[3] = {128, 1, 128 / ST_SPLIT};
        cuuint32_t es[3] = {1, 1, 1};
        enc(&maps.ctxp, CU_TENSOR_MAP_DATA_TYPE_BFLOAT16, 3, p, gd, gs, bx, es, CU_TENSOR_MAP_INTERLEAVE_NONE,
            CU_TENSOR_MAP_SWIZZLE_NONE, CU_TENSOR_MAP_L2_PROMOTION_NONE, CU_TENSOR_MAP_FLOAT_OOB_FILL_NONE);
    }
    fused_decode_kernel<<<NCTA, NTHREADS, SMEM_BYTES>>>((const char*)d_in[9], maps, (const char*)d_in[7], (const char*)d_in[8],
                                                         (const __nv_bfloat16*)d_in[0], (const __nv_bfloat16*)d_in[6],
                                                         (__nv_bfloat16*)d_out, 0u);
}
```

```cpp
#include <cuda_runtime.h>
#include <cuda.h>
#include <cuda_bf16.h>
#include <stdint.h>

#define RING 7
#define WIN 4
#define WHI 5
#define THETA 64
#define END_V 40
#define GATE_W 64
#define PREWIN 3
#define TAILWIN 5
#define POLL_DELAY 2500
#define POLL_DELAY2 4000
#define ST_SPLIT 8
#define ST_GAP 500
#define BACKOFF 200
#define BACKOFF2 100

namespace {

constexpr int NCTA = 128;
constexpr int NTHREADS = 448;
constexpr uint32_t CH = 16384;
constexpr int NTILE = 32;

constexpr uint32_t OFF_RING = 0;
constexpr uint32_t OFF_S0 = RING * CH;
constexpr uint32_t OFF_S1 = OFF_S0 + 2 * CH;
constexpr uint32_t OFF_S2 = OFF_S1 + 2 * CH;
constexpr uint32_t OFF_P = OFF_S2 + 2 * CH;
constexpr uint32_t OFF_SC = OFF_P + 4096;
constexpr uint32_t VROW = 272;
constexpr uint32_t OFF_XB = OFF_SC + 8704;
constexpr uint32_t OFF_XA = OFF_XB + 2 * VROW;
constexpr uint32_t OFF_QA = OFF_XA + 2 * VROW;
constexpr uint32_t OFF_QS = OFF_QA + 2 * VROW;
constexpr uint32_t OFF_CC = OFF_QS + 2 * VROW;
constexpr uint32_t OFF_QB = OFF_CC + 4 * VROW;
constexpr uint32_t YHEAD = 288, YROW = 4 * YHEAD + 16;
constexpr uint32_t OFF_Y = OFF_P;
constexpr uint32_t OFF_PAIR = OFF_P + 2 * YROW;
constexpr uint32_t EMPTY = 0xffffffffu;
constexpr uint32_t OFF_LSE = OFF_QB + 256;
constexpr uint32_t OFF_ML = OFF_LSE + 512;
constexpr uint32_t OFF_TAG = OFF_ML + 32;
constexpr uint32_t OFF_NOW = OFF_TAG + 4;
constexpr uint32_t OFF_WIN = OFF_TAG + 8;
constexpr uint32_t OFF_TWIN = OFF_TAG + 12;
constexpr uint32_t OFF_BAR = OFF_TAG + 16;
constexpr int B_EMPTY = RING;
constexpr int B_WQB = 2 * RING;
constexpr int B_WQA = B_WQB + 2;
constexpr int B_WUK = B_WQA + 2;
constexpr int B_WUV = B_WUK + 2;
constexpr int B_CKV = B_WUV + 2;
constexpr int B_WO = B_CKV + 4;
constexpr int B_FREE = B_WO + 8;
constexpr int B_GATH = B_FREE + 1;
constexpr int B_S2 = B_GATH + 1;
constexpr int NBAR = B_S2 + 1;
constexpr uint32_t TS_OFF = OFF_BAR + NBAR * 8;
constexpr uint32_t SMEM_USED = TS_OFF;
constexpr uint32_t SMEM_BYTES = SMEM_USED + 1024;
static_assert(SMEM_BYTES <= 232448, "smem");
static_assert(RING >= WHI && WHI >= WIN && WIN >= 3 && WIN <= 6, "windows");

constexpr float LOG2E = 1.4426950408889634f;
constexpr float SCALE = 0.08838834764831845f;
#define SPIN_LOG 22
constexpr uint32_t SPIN_MAX = 1u << SPIN_LOG;

struct Maps { CUtensorMap wqB, wqA, wuk, wuv, woA, woB, ckv, ctxp; };

__device__ unsigned g_epoch;
__device__ __align__(256) unsigned g_cnt[96];
__device__ __align__(256) ulonglong2 g_e1[2][NCTA][128];
__device__ __align__(256) uint4 g_qabs[2 * 32 * 64];
__device__ __align__(256) uint4 g_ctxp[NCTA * 128 * 16];
__device__ __align__(256) float4 g_lse[32 * 32];
__device__ __align__(256) ulonglong2 g_e4[NCTA][128];
__device__ __align__(256) uint32_t g_e5[NCTA + 1][128];

#define TS(k) do {} while (0)

__device__ __forceinline__ void mbar_init(uint32_t b, int c) { asm volatile("mbarrier.init.shared::cta.b64 [%0], %1;" ::"r"(b), "r"(c) : "memory"); }
__device__ __forceinline__ void mbar_expect(uint32_t b, uint32_t bytes) { asm volatile("mbarrier.arrive.expect_tx.shared::cta.b64 _, [%0], %1;" ::"r"(b), "r"(bytes) : "memory"); }
__device__ __forceinline__ void mbar_arrive(uint32_t b) { asm volatile("mbarrier.arrive.shared::cta.b64 _, [%0];" ::"r"(b) : "memory"); }
__device__ __forceinline__ void mbar_wait(uint32_t b, uint32_t ph) {
    uint32_t ok, it = 0;
    do {
        asm volatile("{\n.reg .pred p;\nmbarrier.try_wait.parity.shared::cta.b64 p, [%1], %2;\nselp.u32 %0, 1, 0, p;\n}" : "=r"(ok) : "r"(b), "r"(ph) : "memory");
        if (++it > SPIN_MAX) __trap();
    } while (!ok);
}
__device__ __forceinline__ uint32_t mbar_test(uint32_t b, uint32_t ph) {
    uint32_t ok;
    asm volatile("{\n.reg .pred p;\nmbarrier.test_wait.parity.shared::cta.b64 p, [%1], %2;\nselp.u32 %0, 1, 0, p;\n}" : "=r"(ok) : "r"(b), "r"(ph) : "memory");
    return ok;
}
__device__ __forceinline__ void bulk1d(uint32_t dst, const void* src, uint32_t bar, uint64_t pol) {
    asm volatile("cp.async.bulk.shared::cluster.global.mbarrier::complete_tx::bytes.L2::cache_hint [%0], [%1], %2, [%3], %4;"
                 ::"r"(dst), "l"(src), "n"(CH), "r"(bar), "l"(pol) : "memory");
}
__device__ __forceinline__ void bulk1d_n(uint32_t dst, const void* src, uint32_t bytes, uint32_t bar) {
    asm volatile("cp.async.bulk.shared::cluster.global.mbarrier::complete_tx::bytes [%0], [%1], %2, [%3];"
                 ::"r"(dst), "l"(src), "r"(bytes), "r"(bar) : "memory");
}
__device__ __forceinline__ void tma3d(uint32_t dst, const CUtensorMap* map, int c1, int c2, uint32_t bar, uint64_t pol) {
    asm volatile("cp.async.bulk.tensor.3d.shared::cluster.global.mbarrier::complete_tx::bytes.L2::cache_hint [%0], [%1, {%3,%4,%5}], [%2], %6;"
                 ::"r"(dst), "l"(map), "r"(bar), "r"(0), "r"(c1), "r"(c2), "l"(pol) : "memory");
}
__device__ __forceinline__ void bar_sync(int id, int n) { asm volatile("barrier.cta.sync %0, %1;" ::"r"(id), "r"(n) : "memory"); }
__device__ __forceinline__ void bar_arrive(int id, int n) { asm volatile("barrier.cta.arrive %0, %1;" ::"r"(id), "r"(n) : "memory"); }
__device__ __forceinline__ void ldsm4(uint32_t (&r)[4], uint32_t a) {
    asm volatile("ldmatrix.sync.aligned.m8n8.x4.shared.b16 {%0,%1,%2,%3}, [%4];" : "=r"(r[0]), "=r"(r[1]), "=r"(r[2]), "=r"(r[3]) : "r"(a) : "memory");
}
__device__ __forceinline__ void ldsm4t(uint32_t (&r)[4], uint32_t a) {
    asm volatile("ldmatrix.sync.aligned.m8n8.x4.trans.shared.b16 {%0,%1,%2,%3}, [%4];" : "=r"(r[0]), "=r"(r[1]), "=r"(r[2]), "=r"(r[3]) : "r"(a) : "memory");
}
__device__ __forceinline__ void mma(float (&c)[4], const uint32_t (&a)[4], uint32_t b0, uint32_t b1) {
    asm volatile("mma.sync.aligned.m16n8k16.row.col.f32.bf16.bf16.f32 {%0,%1,%2,%3}, {%4,%5,%6,%7}, {%8,%9}, {%0,%1,%2,%3};"
                 : "+f"(c[0]), "+f"(c[1]), "+f"(c[2]), "+f"(c[3]) : "r"(a[0]), "r"(a[1]), "r"(a[2]), "r"(a[3]), "r"(b0), "r"(b1));
}
__device__ __forceinline__ uint32_t lds32(uint32_t a) { uint32_t v; asm volatile("ld.shared.b32 %0, [%1];" : "=r"(v) : "r"(a) : "memory"); return v; }
__device__ __forceinline__ uint32_t ldsv(uint32_t a) { uint32_t v; asm volatile("ld.volatile.shared.b32 %0, [%1];" : "=r"(v) : "r"(a) : "memory"); return v; }
__device__ __forceinline__ void stsv(uint32_t a, uint32_t v) { asm volatile("st.volatile.shared.b32 [%0], %1;" ::"r"(a), "r"(v) : "memory"); }
__device__ __forceinline__ float ldsf(uint32_t a) { float v; asm volatile("ld.shared.f32 %0, [%1];" : "=f"(v) : "r"(a) : "memory"); return v; }
__device__ __forceinline__ uint4 lds128(uint32_t a) { uint4 v; asm volatile("ld.shared.v4.b32 {%0,%1,%2,%3}, [%4];" : "=r"(v.x), "=r"(v.y), "=r"(v.z), "=r"(v.w) : "r"(a) : "memory"); return v; }
__device__ __forceinline__ void sts16(uint32_t a, uint16_t v) { asm volatile("st.shared.b16 [%0], %1;" ::"r"(a), "h"(v) : "memory"); }
__device__ __forceinline__ void sts32(uint32_t a, uint32_t v) { asm volatile("st.shared.b32 [%0], %1;" ::"r"(a), "r"(v) : "memory"); }
__device__ __forceinline__ void stsf2(uint32_t a, float x, float y) { asm volatile("st.shared.v2.f32 [%0], {%1,%2};" ::"r"(a), "f"(x), "f"(y) : "memory"); }
__device__ __forceinline__ void sts128(uint32_t a, uint4 v) { asm volatile("st.shared.v4.b32 [%0], {%1,%2,%3,%4};" ::"r"(a), "r"(v.x), "r"(v.y), "r"(v.z), "r"(v.w) : "memory"); }
__device__ __forceinline__ uint16_t f2bf(float x) { return __bfloat16_as_ushort(__float2bfloat16_rn(x)); }
__device__ __forceinline__ float bfround(float x) { return __bfloat162float(__float2bfloat16_rn(x)); }
__device__ __forceinline__ uint32_t pack2(float lo, float hi) { uint32_t r; asm("cvt.rn.bf16x2.f32 %0, %1, %2;" : "=r"(r) : "f"(hi), "f"(lo)); return r; }
__device__ __forceinline__ float ex2(float x) { float r; asm("ex2.approx.ftz.f32 %0, %1;" : "=f"(r) : "f"(x)); return r; }
__device__ __forceinline__ float lg2(float x) { float r; asm("lg2.approx.ftz.f32 %0, %1;" : "=f"(r) : "f"(x)); return r; }

__device__ __forceinline__ float rcp(float x) { float r; asm("rcp.approx.ftz.f32 %0, %1;" : "=f"(r) : "f"(x)); return r; }

__device__ __forceinline__ void sleep_ns(uint32_t ns) {
    uint32_t t0, t;
    asm volatile("mov.u32 %0, %clock;" : "=r"(t0));
    do { __nanosleep(200); asm volatile("mov.u32 %0, %clock;" : "=r"(t)); } while (t - t0 < 2 * ns);
}

__device__ __forceinline__ void ll_store2(ulonglong2* p, float a, float b, uint32_t tag) {
    unsigned long long x = ((unsigned long long)tag << 32) | __float_as_uint(a);
    unsigned long long y = ((unsigned long long)tag << 32) | __float_as_uint(b);
    asm volatile("st.relaxed.gpu.global.v2.b64 [%0], {%1,%2};" ::"l"(p), "l"(x), "l"(y) : "memory");
}
__device__ __forceinline__ void ll_ld2(const void* p, unsigned long long& x, unsigned long long& y) {
    asm volatile("ld.relaxed.gpu.global.v2.b64 {%0,%1}, [%2];" : "=l"(x), "=l"(y) : "l"(p) : "memory");
}
__device__ __forceinline__ void ll_gather4(const ulonglong2* p, uint32_t tag, float& r0, float& r1) {
    unsigned long long x[4], y[4]; uint32_t it = 0;
    while (true) {
        bool ok = true;
#pragma unroll
        for (int k = 0; k < 4; k++) ll_ld2(p + k * 128, x[k], y[k]);
#pragma unroll
        for (int k = 0; k < 4; k++) ok = ok && (uint32_t)(x[k] >> 32) == tag && (uint32_t)(y[k] >> 32) == tag;
        if (ok) break;
        if (++it > SPIN_MAX) __trap();
        __nanosleep(BACKOFF);
    }
    r0 = (__uint_as_float((uint32_t)x[0]) + __uint_as_float((uint32_t)x[1])) + (__uint_as_float((uint32_t)x[2]) + __uint_as_float((uint32_t)x[3]));
    r1 = (__uint_as_float((uint32_t)y[0]) + __uint_as_float((uint32_t)y[1])) + (__uint_as_float((uint32_t)y[2]) + __uint_as_float((uint32_t)y[3]));
}
__device__ __forceinline__ void cnt_rendezvous(unsigned* c, uint32_t target, int tsk) {
    TS(tsk);
    asm volatile("red.release.gpu.global.add.u32 [%0], 1;" ::"l"(c) : "memory");
    if (tsk == 18) TS(tsk + 1);
    uint32_t v, it = 0;
    while (true) {
        asm volatile("ld.acquire.gpu.global.u32 %0, [%1];" : "=r"(v) : "l"(c) : "memory");
        if ((int)(v - target) >= 0) break;
        if (++it > SPIN_MAX) __trap();
        __nanosleep(BACKOFF);
    }
    asm volatile("fence.proxy.async.global;" ::: "memory");
}

__device__ __forceinline__ void matvec_loadA(uint32_t (&a)[8][4], uint32_t tile, uint32_t bar, int w, int lane) {
    const int i = lane >> 3, rr = lane & 7, chunk = 2 * w + (i & 1);
    const uint32_t a0 = tile + (chunk >> 3) * 8192 + (rr + 8 * (i >> 1)) * 128 + (((chunk & 7) ^ rr) << 4);
#pragma unroll
    for (int hh = 0; hh < 2; hh++) {
        mbar_wait(bar + hh * 8, 0);
#pragma unroll
        for (int k = 0; k < 4; k++) ldsm4t(a[hh * 4 + k], a0 + hh * CH + k * 2048);
    }
}
__device__ __forceinline__ void matvec_mma(float (&c)[4], const uint32_t (&a)[8][4], uint32_t vec, int nvec, int lane) {
    const uint32_t va = vec + (lane & (nvec - 1)) * VROW + (lane >> 3) * 16;
    float d[4][4];
#pragma unroll
    for (int q = 0; q < 4; q++) {
        uint32_t b[4];
        ldsm4(b, va + q * 64);
        d[q][0] = d[q][1] = d[q][2] = d[q][3] = 0.f;
        mma(d[q], a[2 * q], b[0], b[1]);
        mma(d[q], a[2 * q + 1], b[2], b[3]);
    }
#pragma unroll
    for (int k = 0; k < 4; k++) c[k] = (d[0][k] + d[1][k]) + (d[2][k] + d[3][k]);
}
__device__ __forceinline__ void matvecT(float (&c)[4], uint32_t tile, uint32_t vec, int nvec, uint32_t bar, int w, int lane) {
    uint32_t a[8][4];
    matvec_loadA(a, tile, bar, w, lane);
    matvec_mma(c, a, vec, nvec, lane);
}
template <class T> __device__ __forceinline__ T* pin(T* p) { asm volatile("" : "+l"(p)); return p; }
__device__ __forceinline__ void post(uint32_t* p, float v) {
    asm volatile("red.relaxed.gpu.global.add.u32 [%0], %1;" ::"l"(p), "r"(~__float_as_uint(v)) : "memory");
}
__device__ __forceinline__ void ld4_if(const void* p, uint4& x, bool need) {
    asm volatile("{\n.reg .pred q;\nsetp.ne.u32 q, %5, 0;\n@q ld.relaxed.gpu.global.v4.b32 {%0,%1,%2,%3}, [%4];\n}"
                 : "+r"(x.x), "+r"(x.y), "+r"(x.z), "+r"(x.w) : "l"(p), "r"((uint32_t)need) : "memory");
}
__device__ __forceinline__ void merge_store(const uint4 (&x)[5], uint32_t dst) {
#pragma unroll
    for (int b = 0; b < 2; b++) {
        const float l0 = __uint_as_float(~(b ? x[4].z : x[4].x)), l1 = __uint_as_float(~(b ? x[4].w : x[4].y));
        const float mx = fmaxf(l0, l1), e0 = ex2(l0 - mx), e1 = ex2(l1 - mx), r = rcp(e0 + e1);
        const uint4 u = x[2 * b], v = x[2 * b + 1];
        const uint32_t lo = pack2((e0 * __uint_as_float(~u.x) + e1 * __uint_as_float(~v.x)) * r, (e0 * __uint_as_float(~u.y) + e1 * __uint_as_float(~v.y)) * r);
        const uint32_t hi = pack2((e0 * __uint_as_float(~u.z) + e1 * __uint_as_float(~v.z)) * r, (e0 * __uint_as_float(~u.w) + e1 * __uint_as_float(~v.w)) * r);
        asm volatile("st.shared.v2.b32 [%0], {%1,%2};" ::"r"(dst + b * YROW), "r"(lo), "r"(hi) : "memory");
    }
}

__global__ void __launch_bounds__(NTHREADS, 1)
fused_decode_kernel(const char* __restrict__ wqraw, const __grid_constant__ Maps maps, const char* __restrict__ Kc, const char* __restrict__ Vc,
                    const __nv_bfloat16* __restrict__ xA, const __nv_bfloat16* __restrict__ xB,
                    __nv_bfloat16* __restrict__ out, const uint32_t zero) {
    if (threadIdx.x - 32u < 64u) {
        const uint32_t r = threadIdx.x - 32u;
        const uint32_t off = ((blockIdx.x & 3) << 20) + ((blockIdx.x >> 2) << 8) + ((r >> 1) << 13) + ((r & 1) << 7);
        asm volatile("prefetch.global.L2 [%0];" ::"l"(wqraw + off) : "memory");
    }
    extern __shared__ char smem_raw[];
    const uint32_t sm = ((uint32_t)__cvta_generic_to_shared(smem_raw) + 1023u) & ~1023u;
    const uint32_t bars = sm + OFF_BAR;
    const int cta = blockIdx.x, h = cta >> 2, j = cta & 3;
    uint64_t pol = 0;
    if (threadIdx.x == 0) {
        TS(0);
        asm volatile("createpolicy.fractional.L2::evict_first.b64 %0, 1.0;" : "=l"(pol));
#pragma unroll
        for (int i = 0; i < WIN; i++) mbar_init(bars + (B_WQB + i) * 8, 1);
        asm volatile("fence.mbarrier_init.release.cluster;" ::: "memory");
#pragma unroll
        for (int i = 0; i < WIN; i++) {
            mbar_expect(bars + (B_WQB + i) * 8, CH);
            tma3d(sm + OFF_S0 + i * CH, &maps.wqB + (i >> 1), j * 128 + (i & 1) * 64, h * 2, bars + (B_WQB + i) * 8, pol);
        }
    }
    const int tid = threadIdx.x < 64 ? threadIdx.x + 384 : threadIdx.x - 64, warp = tid >> 5, lane = tid & 31;

    if (warp == 12) {
        const size_t kvoff = ((size_t)(((j >> 1) * 32 + h) * 4096 + (j & 1) * 2048)) * 256;
        const char* kp = Kc + kvoff;
        const char* vp = Vc + kvoff;
        __syncwarp();
        bar_arrive(0, NTHREADS);
        bar_sync(3, 64);
        if (lane == 0) {
            uint32_t pb[WHI];
#pragma unroll
            for (int i = 0; i < WHI; i++) pb[i] = i < WHI - WIN ? (bars + B_WO * 8) | 1u : bars + (B_WQB + i - (WHI - WIN)) * 8;
            auto pace = [&](uint32_t bar, uint32_t par, uint32_t wina) {
                uint32_t it = 0;
                while (true) {
                    const uint32_t win = ldsv(wina);
                    uint32_t busy = 0;
#pragma unroll
                    for (int i = 0; i < WHI; i++) busy += mbar_test(pb[i] & ~1u, pb[i] & 1u) ^ 1u;
                    if (busy < win) break;
                    if (++it > SPIN_MAX) __trap();
                }
#pragma unroll
                for (int i = 0; i + 1 < WHI; i++) pb[i] = pb[i + 1];
                pb[WHI - 1] = bar | par;
            };
            auto side = [&](const CUtensorMap* m, uint32_t dst, int bidx, int c1, int c2, uint32_t wina) {
                const uint32_t bar = bars + bidx * 8;
                pace(bar, 0, wina);
                mbar_expect(bar, CH);
                tma3d(dst, m, c1, c2, bar, pol);
            };
#pragma unroll 1
            for (int i = WIN; i < 6; i++)
                side(&maps.wqB + (i >> 1), sm + OFF_S0 + i * CH, B_WQB + i, j * 128 + (i & 1) * 64, h * 2, sm + OFF_WIN);
            TS(1);
            uint32_t slot = 0, use = 0;
            int nuv = 0;
#pragma unroll 1
            for (int n = 0; n < 2 * NTILE; n++) {
                if (n == RING) {
                    mbar_wait(bars + B_FREE * 8, 0);
#pragma unroll 1
                    for (int q = 0; q < 4; q++) side(&maps.ckv, sm + OFF_S0 + q * CH, B_CKV + q, cta * 64 + q * 16, 0, sm + OFF_WIN);
                }
                if (nuv < 2 && n > RING && (n >= 2 * NTILE - 8 || mbar_test(bars + B_FREE * 8, 1))) {
                    mbar_wait(bars + B_FREE * 8, 1);
                    side(&maps.wuv, sm + OFF_S1 + nuv * CH, B_WUV + nuv, j * 128 + nuv * 64, h * 2, sm + OFF_WIN);
                    nuv++;
                }
                const uint32_t fb = bars + slot * 8;
                pace(fb, use & 1, sm + OFF_WIN);
                mbar_wait(fb + B_EMPTY * 8, (use & 1) ^ 1);
                mbar_expect(fb, CH);
                bulk1d(sm + OFF_RING + slot * CH, ((n & 1) ? vp : kp) + (size_t)(n >> 1) * CH, fb, pol);
                asm volatile("red.relaxed.gpu.global.add.u32 [%0], 1;" ::"l"(&g_cnt[64]) : "memory");
                stsv(sm + OFF_NOW, n + 1);
                if (++slot == RING) { slot = 0; use++; }
            }
            TS(2);
            mbar_wait(bars + B_FREE * 8, 0);
            constexpr int NTB = WHI + 1;
            uint32_t tb[NTB];
#pragma unroll
            for (int i = 0; i < NTB; i++) tb[i] = i < NTB - WHI ? bars + B_WQB * 8 : pb[i - (NTB - WHI)] | 2u;
            uint32_t it = 0;
#pragma unroll 1
            for (int q = 0; q < 8;) {
                const uint32_t win = ldsv(sm + OFF_TWIN);
                uint32_t busy = 0;
#pragma unroll
                for (int i = 0; i < NTB; i++) busy += (mbar_test(tb[i] & ~3u, tb[i] & 1u) ^ 1u) << (tb[i] >> 1 & 1u);
#pragma unroll 1
                for (; busy < win && q < 8; busy++, q++) {
                    const uint32_t bar = bars + (B_WO + q) * 8;
                    mbar_expect(bar, CH / 2);
                    tma3d(sm + OFF_S0 + q * (CH / 2), &maps.woA + (cta & 1), (cta >> 4) * 512 + q * 64, (cta >> 1) & 7, bar, pol);
#pragma unroll
                    for (int i = 0; i + 1 < NTB; i++) tb[i] = tb[i + 1];
                    tb[NTB - 1] = bar;
                }
                if (++it > SPIN_MAX) __trap();
            }
            TS(3);
        }
    } else if (warp == 13) {
        if (lane == 0) {
#pragma unroll
            for (int i = 0; i < NBAR; i++)
                if (i < B_WQB || i >= B_WQB + WIN)
                    mbar_init(bars + i * 8, i == B_FREE ? 8 : (i >= B_EMPTY && i < B_EMPTY + RING) ? 4 : 1);
            asm volatile("fence.mbarrier_init.release.cluster;" ::: "memory");
#pragma unroll
            for (int i = 2; i < 8; i++) asm volatile("prefetch.tensormap [%0];" ::"l"(&maps.wqB + i) : "memory");
            stsv(sm + OFF_NOW, 0); stsv(sm + OFF_WIN, WIN); stsv(sm + OFF_TWIN, PREWIN);
        }
        __syncwarp();
        bar_arrive(3, 64);
        bar_sync(0, NTHREADS);
        if (lane == 0) {
            const uint32_t base = (lds32(sm + OFF_TAG) - 1u) * (NCTA * 2 * NTILE);
            mbar_wait(bars + (B_WUK + 1) * 8, 0);
            uint32_t it = 0;
            while (true) {
                const uint32_t n = ldsv(sm + OFF_NOW);
                uint32_t v;
                asm volatile("ld.relaxed.gpu.global.u32 %0, [%1];" : "=r"(v) : "l"(&g_cnt[64]) : "memory");
                v -= base;
                if (v >= NCTA * 2 * NTILE - GATE_W) break;
                const int diff = (int)(n * NCTA) - (int)v;
                stsv(sm + OFF_WIN, diff < -THETA ? WHI : WIN - (diff > THETA) - (v >= NCTA * END_V));
                if (++it > SPIN_MAX) __trap();
                __nanosleep(BACKOFF2);
            }
            stsv(sm + OFF_WIN, WHI); stsv(sm + OFF_TWIN, TAILWIN);
            TS(24);
        }
    } else if (warp < 4) {
        const int g = lane >> 2, t = lane & 3, i = lane >> 3, rr = lane & 7;
        if (tid == 0) {
            const unsigned e = atomicAdd(&g_epoch, 1u);
            sts32(sm + OFF_TAG, (e >> 7) + 1u);
        }
        bar_sync(0, NTHREADS);
        const uint32_t tag = lds32(sm + OFF_TAG);
        {
            mbar_wait(bars + 8, 0);
            float q0, q1;
            ll_gather4(&g_e1[0][h * 4][tid], tag, q0, q1);
            sts16(sm + OFF_QB + tid * 2, f2bf((j >> 1) ? q1 : q0));
        }
        bar_sync(1, 128);
        if (tid == 0) TS(4);
        uint32_t qf[8][2];
#pragma unroll
        for (int c = 0; c < 8; c++) {
            const uint32_t a = sm + OFF_QB + (((c + g) & 7) * 8 + 2 * t) * 2;
            qf[c][0] = lds32(a); qf[c][1] = lds32(a + 128);
        }
        float acc[8][4];
#pragma unroll
        for (int c = 0; c < 8; c++) { acc[c][0] = acc[c][1] = acc[c][2] = acc[c][3] = 0.f; }
        float m = -INFINITY, l = 0.f;
        const bool diag = (t == (g >> 1));
        const uint32_t krow = sm + OFF_RING + (warp * 16 + rr + 8 * (i & 1)) * 256 + (i >> 1) * 128;
        const uint32_t vrow = sm + OFF_RING + (warp * 16 + rr + 8 * (i >> 1)) * 256 + (i & 1) * 128;
        uint32_t slot = 0, ph = 0;
        uint32_t* const e5own = pin(&g_e5[cta][tid]);
        uint32_t a[8][4], b0, b1;
#pragma unroll 1
        for (int tile = 0;; tile++) {
            mbar_wait(bars + slot * 8, ph);
#pragma unroll
            for (int c = 0; c < 8; c++) ldsm4(a[c], krow + slot * CH + (((c + rr) & 7) << 4));
            __syncwarp();
            if (lane == 0) mbar_arrive(bars + (B_EMPTY + slot) * 8 + ((a[0][0] | a[1][0] | a[2][0] | a[3][0] | a[4][0] | a[5][0] | a[6][0] | a[7][0]) & zero));
            if (++slot == RING) { slot = 0; ph ^= 1; }
            float s0[4] = {0.f, 0.f, 0.f, 0.f}, s1[4] = {0.f, 0.f, 0.f, 0.f};
#pragma unroll
            for (int c = 0; c < 8; c += 2) { mma(s0, a[c], qf[c][0], qf[c][1]); mma(s1, a[c + 1], qf[c + 1][0], qf[c + 1][1]); }
            float slo = (g & 1) ? s0[1] + s1[1] : s0[0] + s1[0];
            float shi = (g & 1) ? s0[3] + s1[3] : s0[2] + s1[2];
            slo = diag ? bfround(bfround(slo) * SCALE) : -INFINITY;
            shi = diag ? bfround(bfround(shi) * SCALE) : -INFINITY;
            int key = __float_as_int(fmaxf(slo, shi));
            key ^= (key >> 31) & 0x7fffffff;
            key = __reduce_max_sync(0xffffffffu, key);
            key ^= (key >> 31) & 0x7fffffff;
            const float mn = fmaxf(m, __int_as_float(key));
            const float alpha = ex2((m - mn) * LOG2E);
            m = mn;
            const float plo = ex2((slo - mn) * LOG2E), phi = ex2((shi - mn) * LOG2E);
            l = l * alpha + (plo + phi);
            b0 = (g & 1) ? pack2(0.f, plo) : pack2(plo, 0.f);
            b1 = (g & 1) ? pack2(0.f, phi) : pack2(phi, 0.f);
#pragma unroll
            for (int c = 0; c < 8; c++) { acc[c][0] *= alpha; acc[c][1] *= alpha; acc[c][2] *= alpha; acc[c][3] *= alpha; }
            if (tile == NTILE - 1) break;
            mbar_wait(bars + slot * 8, ph);
#pragma unroll
            for (int c = 0; c < 8; c++) ldsm4t(a[c], vrow + slot * CH + (((c + rr) & 7) << 4));
            __syncwarp();
            if (lane == 0) mbar_arrive(bars + (B_EMPTY + slot) * 8 + ((a[0][0] | a[1][0] | a[2][0] | a[3][0] | a[4][0] | a[5][0] | a[6][0] | a[7][0]) & zero));
            if (++slot == RING) { slot = 0; ph ^= 1; }
#pragma unroll
            for (int c = 0; c < 8; c++) mma(acc[c], a[c], b0, b1);
        }
#pragma unroll
        for (int o = 16; o; o >>= 1) l += __shfl_xor_sync(0xffffffffu, l, o);
        if (lane == 0) stsf2(sm + OFF_ML + warp * 8, m, l);
        mbar_wait(bars + B_S2 * 8, 0);
        bar_sync(1, 128);
        {
            const uint4 ml0 = lds128(sm + OFF_ML), ml1 = lds128(sm + OFF_ML + 16);
            const float m0 = __uint_as_float(ml0.x), m1 = __uint_as_float(ml0.z), m2 = __uint_as_float(ml1.x), m3 = __uint_as_float(ml1.z);
            const float M = fmaxf(fmaxf(m0, m1), fmaxf(m2, m3));
            const float L = (ex2((m0 - M) * LOG2E) * __uint_as_float(ml0.y) + ex2((m1 - M) * LOG2E) * __uint_as_float(ml0.w))
                          + (ex2((m2 - M) * LOG2E) * __uint_as_float(ml1.y) + ex2((m3 - M) * LOG2E) * __uint_as_float(ml1.w));
            const float f = ex2((m - M) * LOG2E) * rcp(L);
            if (tid == 0) post(e5own + (NCTA - cta) * 128 + cta, M * LOG2E + lg2(L));
            mbar_wait(bars + slot * 8, ph);
#pragma unroll
            for (int c = 0; c < 8; c++) ldsm4t(a[c], vrow + slot * CH + (((c + rr) & 7) << 4));
#pragma unroll
            for (int c = 0; c < 8; c++) mma(acc[c], a[c], b0, b1);
            if (tid == 0) TS(5);
            float v[2][8];
#pragma unroll
            for (int c = 0; c < 8; c++) { v[0][c] = acc[c][0] + acc[(c + 7) & 7][1]; v[1][c] = acc[c][2] + acc[(c + 7) & 7][3]; }
#pragma unroll
            for (int c = 0; c < 4; c++) { v[0][c] += __shfl_xor_sync(0xffffffffu, v[0][c + 4], 2); v[1][c] += __shfl_xor_sync(0xffffffffu, v[1][c + 4], 2); }
            const int src = (lane & ~3) | ((lane + 3) & 3);
#pragma unroll
            for (int c = 0; c < 2; c++) { v[0][c] += __shfl_sync(0xffffffffu, v[0][c + 2], src); v[1][c] += __shfl_sync(0xffffffffu, v[1][c + 2], src); }
            const uint32_t wa = sm + OFF_S2 + (warp * 160 + 16 * t + 8 * (t >> 1) + g) * 4;
            sts32(wa, __float_as_uint(v[0][0] * f)); sts32(wa + 32, __float_as_uint(v[0][1] * f));
            sts32(wa + 320, __float_as_uint(v[1][0] * f)); sts32(wa + 352, __float_as_uint(v[1][1] * f));
            bar_sync(1, 128);
            const uint32_t ra = sm + OFF_S2 + (tid + warp * 8) * 4;
            post(e5own, (ldsf(ra) + ldsf(ra + 640)) + (ldsf(ra + 1280) + ldsf(ra + 1920)));
        }
        if (tid == 0) TS(6);
        if (cta & 1) {
            const int c0 = (cta & ~15) + warp * 4;
            const uint32_t* p = e5own + ((c0 - cta) * 128 + lane * 4 - tid);
            const uint32_t* pl = e5own + ((NCTA - cta) * 128 + c0 - tid);
            uint4 x[5];
            bool need[5] = {true, true, true, true, true};
            uint32_t it = 0;
            while (true) {
#pragma unroll
                for (int q = 0; q < 5; q++) ld4_if(q < 4 ? p + q * 128 : pl, x[q], need[q]);
#pragma unroll
                for (int q = 0; q < 5; q++) need[q] = !x[q].x || !x[q].y || !x[q].z || !x[q].w;
                if (!__any_sync(0xffffffffu, need[0] | need[1] | need[2] | need[3] | need[4])) break;
                if (++it > SPIN_MAX) __trap();
            }
            merge_store(x, sm + OFF_Y + warp * YHEAD + lane * 8);
            bar_arrive(4, 256 + 128);
        }
        if (tid == 0) TS(16);
    } else {
        const int st = tid - 128, w = warp - 4;
        const int g = lane >> 2, t = lane & 3, i = lane >> 3, rr = lane & 7;
        if (t == 0) {
#pragma unroll
            for (int k = 0; k < 4; k++) ll_store2(&g_e1[k >> 1][cta][w * 16 + g + (k & 1) * 8], 0.f, 0.f, 0u);
        }
        if (st < 64) {
            const int which = st >> 5, b = (st >> 4) & 1, c = st & 15;
            const uint4 v = __ldg((const uint4*)((which ? xA : xB) + b * 512 + j * 128) + c);
            sts128(sm + OFF_XB + (which * 2 + b) * VROW + c * 16, v);
        }
        bar_sync(0, NTHREADS);
        const uint32_t tag = lds32(sm + OFF_TAG);
        float c[4];
#pragma unroll 1
        for (int which = 0; which < 2; which++) {
            matvecT(c, sm + OFF_S0 + which * 2 * CH, sm + OFF_XB + which * 2 * VROW, 2, bars + (B_WQB + which * 2) * 8, w, lane);
            if (t == 0) {
                ll_store2(&g_e1[which][cta][w * 16 + g], c[0], c[1], tag);
                ll_store2(&g_e1[which][cta][w * 16 + g + 8], c[2], c[3], tag);
            }
        }
        __syncwarp();
        if (lane == 0) mbar_arrive(bars + B_FREE * 8);
        if (st == 0) TS(8);
        if (st < 128) {
            float q0, q1;
            sleep_ns(POLL_DELAY);
            ll_gather4(&g_e1[1][h * 4][st], tag, q0, q1);
            sts16(sm + OFF_QA + st * 2, f2bf(q0)); sts16(sm + OFF_QA + VROW + st * 2, f2bf(q1));
        }
        bar_sync(2, 256);
        if (st == 0) TS(9);
        {
            const int row = w * 16 + rr + 8 * (i & 1);
            const uint32_t a0 = sm + OFF_S2 + (row >> 6) * CH + (row & 63) * 128;
            const uint32_t va = sm + OFF_QA + g * VROW + t * 4;
            float d[4] = {0.f, 0.f, 0.f, 0.f};
            c[0] = c[1] = c[2] = c[3] = 0.f;
            mbar_wait(bars + (B_WUK + (w >> 2)) * 8, 0);
#pragma unroll
            for (int ks = 0; ks < 8; ks++) {
                const int chunk = 2 * ks + (i >> 1);
                uint32_t a[4];
                ldsm4(a, a0 + (chunk >> 3) * 8192 + (((chunk & 7) ^ rr) << 4));
                const uint32_t b0 = (g < 2) ? lds32(va + ks * 32) : 0u, b1 = (g < 2) ? lds32(va + ks * 32 + 16) : 0u;
                if (ks & 1) mma(d, a, b0, b1); else mma(c, a, b0, b1);
            }
            if (t == 0) {
                const uint32_t qs = sm + OFF_QS + (w * 16 + g) * 2;
                sts16(qs, f2bf(c[0] + d[0])); sts16(qs + VROW, f2bf(c[1] + d[1]));
                sts16(qs + 16, f2bf(c[2] + d[2])); sts16(qs + VROW + 16, f2bf(c[3] + d[3]));
            }
            bar_sync(2, 256);
            if (w == 0) {
                const int b = lane >> 4, cc = lane & 15;
                g_qabs[(b * 32 + h) * 64 + ((j * 16 + cc) ^ (h & 7))] = lds128(sm + OFF_QS + b * VROW + cc * 16);
                __syncwarp();
                if (lane == 0) {
                    cnt_rendezvous(&g_cnt[0], tag * 128u, 18);
                    TS(10);
                    mbar_expect(bars + B_GATH * 8, 2 * CH);
                    bulk1d_n(sm + OFF_S2, g_qabs + (cta >> 6) * 2048, 2 * CH, bars + B_GATH * 8);
                }
                __syncwarp();
            }
        }
        mbar_wait(bars + B_GATH * 8, 0);
        if (st == 0) TS(11);
        {
            const int mt = w & 1, kg = w >> 1;
            const uint32_t qa = sm + OFF_S2 + (mt * 16 + rr + 8 * (i & 1)) * 1024;
            const uint32_t ka = sm + OFF_S0 + kg * CH + (rr + 8 * (i >> 1)) * 128;
            float s0[4] = {0.f, 0.f, 0.f, 0.f}, s1[4] = {0.f, 0.f, 0.f, 0.f};
            mbar_wait(bars + (B_CKV + kg) * 8, 0);
#pragma unroll 2
            for (int gq = 0; gq < 8; gq++) {
#pragma unroll
                for (int k4 = 0; k4 < 4; k4++) {
                    uint32_t a[4], b[4];
                    ldsm4(a, qa + gq * 128 + (((2 * k4 + (i >> 1)) ^ rr) << 4));
                    ldsm4(b, ka + gq * 2048 + (((2 * k4 + (i & 1)) ^ rr) << 4));
                    mma(s0, a, b[0], b[1]);
                    mma(s1, a, b[2], b[3]);
                }
            }
            const uint32_t sa = sm + OFF_SC + ((mt * 16 + g) * 68 + kg * 16 + 2 * t) * 4;
            stsf2(sa, s0[0], s0[1]); stsf2(sa + 32, s1[0], s1[1]);
            stsf2(sa + 8 * 68 * 4, s0[2], s0[3]); stsf2(sa + 8 * 68 * 4 + 32, s1[2], s1[3]);
        }
        bar_sync(2, 256);
        {
            const int head = w * 4 + i;
            const uint32_t sa = sm + OFF_SC + (head * 68 + rr * 8) * 4;
            const uint4 u0 = lds128(sa), u1 = lds128(sa + 16);
            float s[8] = {__uint_as_float(u0.x), __uint_as_float(u0.y), __uint_as_float(u0.z), __uint_as_float(u0.w),
                          __uint_as_float(u1.x), __uint_as_float(u1.y), __uint_as_float(u1.z), __uint_as_float(u1.w)};
            float mx = s[0];
#pragma unroll
            for (int k = 1; k < 8; k++) mx = fmaxf(mx, s[k]);
#pragma unroll
            for (int o = 1; o < 8; o <<= 1) mx = fmaxf(mx, __shfl_xor_sync(0xffffffffu, mx, o));
            float sum = 0.f;
#pragma unroll
            for (int k = 0; k < 8; k++) { s[k] = ex2((s[k] - mx) * (SCALE * LOG2E)); sum += s[k]; }
#pragma unroll
            for (int o = 1; o < 8; o <<= 1) sum += __shfl_xor_sync(0xffffffffu, sum, o);
            const float inv = __fdividef(1.f, sum);
            uint4 p;
            p.x = pack2(s[0] * inv, s[1] * inv); p.y = pack2(s[2] * inv, s[3] * inv);
            p.z = pack2(s[4] * inv, s[5] * inv); p.w = pack2(s[6] * inv, s[7] * inv);
            sts128(sm + OFF_P + head * 128 + ((rr ^ (head & 7)) << 4), p);
            if (rr == 0) ((float*)g_lse)[head * 128 + cta] = mx * (SCALE * LOG2E) + lg2(sum);
        }
        bar_sync(2, 256);
        {
            float o[2][8][4];
#pragma unroll
            for (int mt = 0; mt < 2; mt++)
#pragma unroll
                for (int n = 0; n < 8; n++) { o[mt][n][0] = o[mt][n][1] = o[mt][n][2] = o[mt][n][3] = 0.f; }
            const uint32_t pa = sm + OFF_P + (rr + 8 * (i & 1)) * 128;
            const uint32_t va = sm + OFF_S0 + w * 2048 + (rr + 8 * (i & 1)) * 128;
#pragma unroll 1
            for (int kq = 0; kq < 4; kq++) {
                uint32_t a0[4], a1[4];
                ldsm4(a0, pa + (((2 * kq + (i >> 1)) ^ rr) << 4));
                ldsm4(a1, pa + 2048 + (((2 * kq + (i >> 1)) ^ rr) << 4));
#pragma unroll
                for (int n = 0; n < 8; n += 2) {
                    uint32_t b[4];
                    ldsm4t(b, va + kq * CH + (((n + (i >> 1)) ^ rr) << 4));
                    mma(o[0][n], a0, b[0], b[1]); mma(o[1][n], a1, b[0], b[1]);
                    mma(o[0][n + 1], a0, b[2], b[3]); mma(o[1][n + 1], a1, b[2], b[3]);
                }
            }
#pragma unroll
            for (int mt = 0; mt < 2; mt++)
#pragma unroll
                for (int hf = 0; hf < 2; hf++) {
                    const uint32_t dst = sm + OFF_S2 + (mt * 16 + hf * 8 + g) * 1024 + w * 128 + t * 16;
#pragma unroll
                    for (int nb = 0; nb < 2; nb++) {
                        uint4 v;
                        v.x = pack2(o[mt][nb * 4 + 0][hf * 2], o[mt][nb * 4 + 0][hf * 2 + 1]);
                        v.y = pack2(o[mt][nb * 4 + 1][hf * 2], o[mt][nb * 4 + 1][hf * 2 + 1]);
                        v.z = pack2(o[mt][nb * 4 + 2][hf * 2], o[mt][nb * 4 + 2][hf * 2 + 1]);
                        v.w = pack2(o[mt][nb * 4 + 3][hf * 2], o[mt][nb * 4 + 3][hf * 2 + 1]);
                        sts128(dst + nb * 64, v);
                    }
                }
            asm volatile("fence.proxy.async.shared::cta;" ::: "memory");
            __syncwarp();
            if (lane == 0) mbar_arrive(bars + B_FREE * 8);
            if (t == 0) { ll_store2(&g_e4[cta][w * 16 + g], 0.f, 0.f, 0u); ll_store2(&g_e4[cta][w * 16 + g + 8], 0.f, 0.f, 0u); }
            if (st < 128) g_e5[cta][st] = 0u;
            else if (cta == 0) g_e5[NCTA][st - 128] = 0u;
            if (st >= 248) ((uint32_t*)out)[cta * 8 + st - 248] = 0u;
        }
        bar_sync(2, 256);
        if (st == 0) {
            TS(12);
#pragma unroll 1
            for (int k = 0; k < ST_SPLIT; k++) {
                asm volatile("cp.async.bulk.tensor.3d.global.shared::cta.bulk_group [%0, {%2,%3,%4}], [%1];"
                             ::"l"(&maps.ctxp), "r"(sm + OFF_S2 + k * (2 * CH / ST_SPLIT)), "r"(0), "r"(cta), "r"(k * (128 / ST_SPLIT)) : "memory");
                if (k + 1 < ST_SPLIT) __nanosleep(ST_GAP);
            }
            asm volatile("cp.async.bulk.commit_group;" ::: "memory");
            asm volatile("cp.async.bulk.wait_group 0;" ::: "memory");
            cnt_rendezvous(&g_cnt[32], tag * 128u, 20);
            TS(13);
            mbar_expect(bars + B_GATH * 8, 2 * CH + 512);
            bulk1d_n(sm + OFF_LSE, g_lse + h * 32, 512, bars + B_GATH * 8);
            bulk1d_n(sm + OFF_S2, g_ctxp + cta * 2048, 2 * CH, bars + B_GATH * 8);
        }
        __syncwarp();
        {
            mbar_wait(bars + B_GATH * 8, 1);
            if (st == 0) TS(22);
            uint4 v[8];
#pragma unroll
            for (int k = 0; k < 8; k++) v[k] = lds128(sm + OFF_S2 + (k * 256 + st) * 16);
            float ls[4];
#pragma unroll
            for (int k = 0; k < 4; k++) ls[k] = ldsf(sm + OFF_LSE + (k * 32 + lane) * 4);
            float m0 = fmaxf(ls[0], ls[1]), m1 = fmaxf(ls[2], ls[3]);
#pragma unroll
            for (int o = 16; o; o >>= 1) { m0 = fmaxf(m0, __shfl_xor_sync(0xffffffffu, m0, o)); m1 = fmaxf(m1, __shfl_xor_sync(0xffffffffu, m1, o)); }
            ls[0] = ex2(ls[0] - m0); ls[1] = ex2(ls[1] - m0); ls[2] = ex2(ls[2] - m1); ls[3] = ex2(ls[3] - m1);
            float z0 = ls[0] + ls[1], z1 = ls[2] + ls[3];
#pragma unroll
            for (int o = 16; o; o >>= 1) { z0 += __shfl_xor_sync(0xffffffffu, z0, o); z1 += __shfl_xor_sync(0xffffffffu, z1, o); }
            z0 = __fdividef(1.f, z0); z1 = __fdividef(1.f, z1);
            ls[0] *= z0; ls[1] *= z0; ls[2] *= z1; ls[3] *= z1;
            float a[2][8];
#pragma unroll
            for (int e = 0; e < 8; e++) a[0][e] = a[1][e] = 0.f;
            const int rg = st >> 4;
#pragma unroll
            for (int k = 0; k < 8; k++) {
                const float wt = __shfl_sync(0xffffffffu, ls[k >> 1], rg + 16 * (k & 1));
                const uint32_t u[4] = {v[k].x, v[k].y, v[k].z, v[k].w};
#pragma unroll
                for (int e = 0; e < 4; e++) {
                    a[k >> 2][2 * e] += wt * __uint_as_float(u[e] << 16);
                    a[k >> 2][2 * e + 1] += wt * __uint_as_float(u[e] & 0xffff0000u);
                }
            }
            const int b = lane >> 4, u16 = lane & 15;
            const uint32_t ra = sm + OFF_SC + (w * 256 + b * 128 + (u16 >> 3) * 64 + ((u16 >> 2) & 1) * 32 + (u16 & 3) * 2) * 4;
#pragma unroll
            for (int e = 0; e < 8; e += 2) {
                const float k0 = b ? a[1][e] : a[0][e], k1 = b ? a[1][e + 1] : a[0][e + 1];
                const float s0 = b ? a[0][e] : a[1][e], s1 = b ? a[0][e + 1] : a[1][e + 1];
                stsf2(ra + (e >> 1) * 32, k0 + __shfl_xor_sync(0xffffffffu, s0, 16), k1 + __shfl_xor_sync(0xffffffffu, s1, 16));
            }
            bar_sync(2, 256);
            if (st == 0) mbar_arrive(bars + B_S2 * 8);
            float s = 0.f;
#pragma unroll
            for (int k = 0; k < 8; k++) s += ldsf(sm + OFF_SC + (k * 256 + st) * 4);
            const float hi = bfround(s);
            const uint32_t ca = sm + OFF_CC + (st >> 7) * VROW + (st & 127) * 2;
            sts16(ca, f2bf(hi)); sts16(ca + 2 * VROW, f2bf(s - hi));
            bar_sync(2, 256);
        }
        matvecT(c, sm + OFF_S1, sm + OFF_CC, 4, bars + B_WUV * 8, w, lane);
#pragma unroll
        for (int k = 0; k < 4; k++) c[k] += __shfl_down_sync(0xffffffffu, c[k], 1);
        if (t == 0) {
            ll_store2(&g_e4[cta][w * 16 + g], c[0], c[1], tag);
            ll_store2(&g_e4[cta][w * 16 + g + 8], c[2], c[3], tag);
        }
        __syncwarp();
        if (lane == 0) mbar_arrive(bars + B_FREE * 8);
        if (st == 0) TS(23);
        if (st < 128) sts32(sm + OFF_PAIR + st * 4, EMPTY);
        if (!(cta & 1)) {
            sleep_ns(POLL_DELAY2);
#pragma unroll 1
            for (int e = st; e < 512; e += 256) {
                float q0, q1;
                ll_gather4(&g_e4[(cta & ~15) + (e >> 7) * 4][e & 127], tag, q0, q1);
                const uint32_t ya = sm + OFF_Y + (e >> 7) * YHEAD + (e & 127) * 2;
                sts16(ya, f2bf(q0)); sts16(ya + YROW, f2bf(q1));
            }
        }
        if (st == 0) TS(14);
        bar_sync(2, 256);
        {
            const int hf = w >> 2, cg = w & 3;
            const uint32_t a0 = sm + OFF_S0 + hf * 8192 + (rr + 8 * (i >> 1)) * 128 + (((2 * cg + (i & 1)) ^ rr) << 4);
            const uint32_t va = sm + OFF_Y + (lane >> 1 & 1) * YROW + (lane & 1) * YHEAD + hf * 128 + i * 16;
            const uint32_t wb = bars + (B_WO + hf) * 8;
            const uint32_t pa = sm + OFF_PAIR + (cg * 32 + lane) * 4;
            const int col = (t & 1) * 1024 + (cta & 1) * 512 + (cta >> 1 & 7) * 64 + cg * 16 + (t >> 1) * 8 + g;
            __nv_bfloat16* const outp = pin(out + (col & ~1));
            const bool up = t >= 2, odd = g & 1;
            uint32_t a[4][4][4], b[4][4];
            float d[2][4][4];
#pragma unroll
            for (int k = 0; k < 8; k++) d[k >> 2][k & 3][0] = d[k >> 2][k & 3][1] = d[k >> 2][k & 3][2] = d[k >> 2][k & 3][3] = 0.f;
            auto load_w = [&](int hd) {
                mbar_wait(wb + hd * 16, 0);
#pragma unroll
                for (int k = 0; k < 4; k++) ldsm4t(a[hd][k], a0 + hd * CH + k * 2048);
            };
            auto load_y = [&]() {
#pragma unroll
                for (int q = 0; q < 4; q++) ldsm4(b[q], va + (q >> 1) * 2 * YHEAD + (q & 1) * 64);
            };
            auto head = [&](int hd) {
#pragma unroll
                for (int k = 0; k < 4; k++) mma(d[hd & 1][k], a[hd][k], b[(hd & 2) + (k >> 1)][(k & 1) * 2], b[(hd & 2) + (k >> 1)][(k & 1) * 2 + 1]);
            };
            if (cta & 1) {
                load_w(0); load_w(1);
                bar_sync(4, 256 + 128);
                load_y();
                head(0); head(1);
            } else {
                load_y();
                load_w(0); head(0);
                load_w(1); head(1);
            }
            if (st == 0) TS(25);
            load_w(2); head(2);
            float z = up ? (d[0][0][2] + d[0][1][2]) + (d[0][2][2] + d[0][3][2]) : (d[0][0][0] + d[0][1][0]) + (d[0][2][0] + d[0][3][0]);
            load_w(3);
            if (st == 0) TS(26);
            uint32_t other = ldsv(pa);
            head(3);
            z += other != EMPTY ? __uint_as_float(other) : 0.f;
            z = up ? ((z + d[1][0][3]) + d[1][1][3]) + (d[1][2][3] + d[1][3][3]) : ((z + d[1][0][1]) + d[1][1][1]) + (d[1][2][1] + d[1][3][1]);
            if (st == 0) TS(17);
            asm volatile("{\n.reg .pred p;\nsetp.ne.u32 p, %2, %3;\n@p red.relaxed.gpu.global.add.noftz.bf16x2 [%0], %1;\n@p exit;\n}"
                         ::"l"(outp), "r"(odd ? pack2(0.f, z) : pack2(z, 0.f)), "r"(other), "n"(EMPTY) : "memory");
            {
                asm volatile("atom.shared.exch.b32 %0, [%1], %2;" : "=r"(other) : "r"(pa), "r"(__float_as_uint(z)) : "memory");
                z += __uint_as_float(other);
            }
            if (other != EMPTY)
                asm volatile("red.relaxed.gpu.global.add.noftz.bf16x2 [%0], %1;" ::"l"(outp), "r"(odd ? pack2(0.f, z) : pack2(z, 0.f)) : "memory");
        }
    }
}

typedef CUresult (*EncodeFn)(CUtensorMap*, CUtensorMapDataType, cuuint32_t, void*, const cuuint64_t*, const cuuint64_t*,
                             const cuuint32_t*, const cuuint32_t*, CUtensorMapInterleave, CUtensorMapSwizzle,
                             CUtensorMapL2promotion, CUtensorMapFloatOOBfill);

void make_map(EncodeFn enc, CUtensorMap* m, void* p, unsigned rows, unsigned cols, unsigned br, unsigned bg) {
    cuuint64_t gd[3] = {64, rows, cols / 64};
    cuuint64_t gs[2] = {(cuuint64_t)cols * 2, 128};
    cuuint32_t bx[3] = {64, br, bg};
    cuuint32_t es[3] = {1, 1, 1};
    enc(m, CU_TENSOR_MAP_DATA_TYPE_BFLOAT16, 3, p, gd, gs, bx, es, CU_TENSOR_MAP_INTERLEAVE_NONE,
        CU_TENSOR_MAP_SWIZZLE_128B, CU_TENSOR_MAP_L2_PROMOTION_L2_128B, CU_TENSOR_MAP_FLOAT_OOB_FILL_NONE);
}

}

extern "C" void kernel_launch(void* const* d_in, const int* in_sizes, int n_in, void* d_out, int out_size) {
    static EncodeFn enc = nullptr;
    if (!enc) {
        void* fn = nullptr;
        cudaDriverEntryPointQueryResult qr;
        cudaGetDriverEntryPoint("cuTensorMapEncodeTiled", &fn, cudaEnableDefault, &qr);
        enc = (EncodeFn)fn;
        cudaFuncSetAttribute(fused_decode_kernel, cudaFuncAttributeMaxDynamicSharedMemorySize, SMEM_BYTES);
    }
    Maps maps;
    make_map(enc, &maps.wqB, d_in[9], 512, 4096, 64, 2);
    make_map(enc, &maps.wqA, d_in[2], 512, 4096, 64, 2);
    make_map(enc, &maps.wuk, d_in[3], 512, 4096, 64, 2);
    make_map(enc, &maps.wuv, d_in[4], 512, 4096, 64, 2);
    make_map(enc, &maps.woA, d_in[5], 4096, 512, 64, 1);
    make_map(enc, &maps.woB, d_in[10], 4096, 512, 64, 1);
    make_map(enc, &maps.ckv, d_in[1], 8192, 512, 16, 8);
    {
        void* p = nullptr;
        cudaGetSymbolAddress(&p, g_ctxp);
        cuuint64_t gd[3] = {128, 128, 128};
        cuuint64_t gs[2] = {256, 32768};
        cuuint32_t bx[3] = {128, 1, 128 / ST_SPLIT};
        cuuint32_t es[3] = {1, 1, 1};
        enc(&maps.ctxp, CU_TENSOR_MAP_DATA_TYPE_BFLOAT16, 3, p, gd, gs, bx, es, CU_TENSOR_MAP_INTERLEAVE_NONE,
            CU_TENSOR_MAP_SWIZZLE_NONE, CU_TENSOR_MAP_L2_PROMOTION_NONE, CU_TENSOR_MAP_FLOAT_OOB_FILL_NONE);
    }
    fused_decode_kernel<<<NCTA, NTHREADS, SMEM_BYTES>>>((const char*)d_in[9], maps, (const char*)d_in[7], (const char*)d_in[8],
                                                         (const __nv_bfloat16*)d_in[0], (const __nv_bfloat16*)d_in[6],
                                                         (__nv_bfloat16*)d_out, 0u);
}
```

```cpp
#include <cuda_runtime.h>
#include <cuda.h>
#include <cuda_bf16.h>
#include <stdint.h>

#define RING 7
#define WIN 4
#define WHI 5
#define THETA 64
#define END_V 40
#define GATE_W 64
#define PREWIN 3
#define TAILWIN 5
#define POLL_DELAY 2500
#define POLL_DELAY2 2500
#define ST_SPLIT 8
#define ST_GAP 500
#define LD_GAP 300
#define BACKOFF 200
#define BACKOFF_RV 800
#define FINE_V 52
#define BACKOFF2 100
#define BACKOFF3 300

namespace {

constexpr int NCTA = 128;
constexpr int NTHREADS = 448;
constexpr uint32_t CH = 16384;
constexpr int NTILE = 32;

constexpr uint32_t OFF_RING = 0;
constexpr uint32_t OFF_S0 = RING * CH;
constexpr uint32_t OFF_S1 = OFF_S0 + 2 * CH;
constexpr uint32_t OFF_S2 = OFF_S1 + 2 * CH;
constexpr uint32_t OFF_P = OFF_S2 + 2 * CH;
constexpr uint32_t OFF_SC = OFF_P + 4096;
constexpr uint32_t VROW = 272;
constexpr uint32_t OFF_XB = OFF_SC + 8704;
constexpr uint32_t OFF_XA = OFF_XB + 2 * VROW;
constexpr uint32_t OFF_QA = OFF_XA + 2 * VROW;
constexpr uint32_t OFF_QS = OFF_QA + 2 * VROW;
constexpr uint32_t OFF_CC = OFF_QS + 2 * VROW;
constexpr uint32_t OFF_QB = OFF_CC + 4 * VROW;
constexpr uint32_t YHEAD = 288, YROW = 4 * YHEAD + 16;
constexpr uint32_t OFF_Y = OFF_P;
constexpr uint32_t OFF_PAIR = OFF_P + 2 * YROW;
constexpr uint32_t EMPTY = 0xffffffffu;
constexpr uint32_t OFF_LSE = OFF_QB + 256;
constexpr uint32_t OFF_ML = OFF_LSE + 512;
constexpr uint32_t OFF_TAG = OFF_ML + 32;
constexpr uint32_t OFF_NOW = OFF_TAG + 4;
constexpr uint32_t OFF_WIN = OFF_TAG + 8;
constexpr uint32_t OFF_TWIN = OFF_TAG + 12;
constexpr uint32_t OFF_BAR = OFF_TAG + 16;
constexpr int B_EMPTY = RING;
constexpr int B_WQB = 2 * RING;
constexpr int B_WQA = B_WQB + 2;
constexpr int B_WUK = B_WQA + 2;
constexpr int B_WUV = B_WUK + 2;
constexpr int B_CKV = B_WUV + 2;
constexpr int B_WO = B_CKV + 4;
constexpr int B_FREE = B_WO + 8;
constexpr int B_GATH = B_FREE + 1;
constexpr int B_S2 = B_GATH + 1;
constexpr int NBAR = B_S2 + 1;
constexpr uint32_t TS_OFF = OFF_BAR + NBAR * 8;
constexpr uint32_t SMEM_USED = TS_OFF;
constexpr uint32_t SMEM_BYTES = SMEM_USED + 1024;
static_assert(SMEM_BYTES <= 232448, "smem");
static_assert(RING >= WHI && WHI >= WIN && WIN >= 3 && WIN <= 6 && FINE_V % 2 == 0, "windows");

constexpr float LOG2E = 1.4426950408889634f;
constexpr float SCALE = 0.08838834764831845f;
#define SPIN_LOG 22
constexpr uint32_t SPIN_MAX = 1u << SPIN_LOG;

struct Maps { CUtensorMap wqB, wqA, wuk, wuv, woA, woB, ckv, ctxp; };

__device__ __align__(256) unsigned g_cnt[4];
__device__ __align__(256) ulonglong2 g_e1[2][NCTA][128];
__device__ __align__(256) uint4 g_qabs[2 * 32 * 64];
__device__ __align__(256) uint4 g_ctxp[NCTA * 128 * 16];
__device__ __align__(256) float4 g_lse[32 * 32];
__device__ __align__(256) uint32_t g_e4[NCTA][256];
__device__ __align__(256) uint32_t g_e5[NCTA + 1][128];

#define TS(k) do {} while (0)

__device__ __forceinline__ void mbar_init(uint32_t b, int c) { asm volatile("mbarrier.init.shared::cta.b64 [%0], %1;" ::"r"(b), "r"(c) : "memory"); }
__device__ __forceinline__ void mbar_expect(uint32_t b, uint32_t bytes) { asm volatile("mbarrier.arrive.expect_tx.shared::cta.b64 _, [%0], %1;" ::"r"(b), "r"(bytes) : "memory"); }
__device__ __forceinline__ void mbar_arrive(uint32_t b) { asm volatile("mbarrier.arrive.shared::cta.b64 _, [%0];" ::"r"(b) : "memory"); }
__device__ __forceinline__ void mbar_wait(uint32_t b, uint32_t ph) {
    uint32_t ok, it = 0;
    do {
        asm volatile("{\n.reg .pred p;\nmbarrier.try_wait.parity.shared::cta.b64 p, [%1], %2;\nselp.u32 %0, 1, 0, p;\n}" : "=r"(ok) : "r"(b), "r"(ph) : "memory");
        if (++it > SPIN_MAX) __trap();
    } while (!ok);
}
__device__ __forceinline__ uint32_t mbar_test(uint32_t b, uint32_t ph) {
    uint32_t ok;
    asm volatile("{\n.reg .pred p;\nmbarrier.test_wait.parity.shared::cta.b64 p, [%1], %2;\nselp.u32 %0, 1, 0, p;\n}" : "=r"(ok) : "r"(b), "r"(ph) : "memory");
    return ok;
}
__device__ __forceinline__ void bulk1d(uint32_t dst, const void* src, uint32_t bar, uint64_t pol) {
    asm volatile("cp.async.bulk.shared::cluster.global.mbarrier::complete_tx::bytes.L2::cache_hint [%0], [%1], %2, [%3], %4;"
                 ::"r"(dst), "l"(src), "n"(CH), "r"(bar), "l"(pol) : "memory");
}
__device__ __forceinline__ void bulk1d_n(uint32_t dst, const void* src, uint32_t bytes, uint32_t bar) {
    asm volatile("cp.async.bulk.shared::cluster.global.mbarrier::complete_tx::bytes [%0], [%1], %2, [%3];"
                 ::"r"(dst), "l"(src), "r"(bytes), "r"(bar) : "memory");
}
__device__ __forceinline__ void tma3d(uint32_t dst, const CUtensorMap* map, int c1, int c2, uint32_t bar, uint64_t pol) {
    asm volatile("cp.async.bulk.tensor.3d.shared::cluster.global.mbarrier::complete_tx::bytes.L2::cache_hint [%0], [%1, {%3,%4,%5}], [%2], %6;"
                 ::"r"(dst), "l"(map), "r"(bar), "r"(0), "r"(c1), "r"(c2), "l"(pol) : "memory");
}
__device__ __forceinline__ void bar_sync(int id, int n) { asm volatile("barrier.cta.sync %0, %1;" ::"r"(id), "r"(n) : "memory"); }
__device__ __forceinline__ void bar_arrive(int id, int n) { asm volatile("barrier.cta.arrive %0, %1;" ::"r"(id), "r"(n) : "memory"); }
__device__ __forceinline__ void ldsm4(uint32_t (&r)[4], uint32_t a) {
    asm volatile("ldmatrix.sync.aligned.m8n8.x4.shared.b16 {%0,%1,%2,%3}, [%4];" : "=r"(r[0]), "=r"(r[1]), "=r"(r[2]), "=r"(r[3]) : "r"(a) : "memory");
}
__device__ __forceinline__ void ldsm4t(uint32_t (&r)[4], uint32_t a) {
    asm volatile("ldmatrix.sync.aligned.m8n8.x4.trans.shared.b16 {%0,%1,%2,%3}, [%4];" : "=r"(r[0]), "=r"(r[1]), "=r"(r[2]), "=r"(r[3]) : "r"(a) : "memory");
}
__device__ __forceinline__ void mma(float (&c)[4], const uint32_t (&a)[4], uint32_t b0, uint32_t b1) {
    asm volatile("mma.sync.aligned.m16n8k16.row.col.f32.bf16.bf16.f32 {%0,%1,%2,%3}, {%4,%5,%6,%7}, {%8,%9}, {%0,%1,%2,%3};"
                 : "+f"(c[0]), "+f"(c[1]), "+f"(c[2]), "+f"(c[3]) : "r"(a[0]), "r"(a[1]), "r"(a[2]), "r"(a[3]), "r"(b0), "r"(b1));
}
__device__ __forceinline__ uint32_t lds32(uint32_t a) { uint32_t v; asm volatile("ld.shared.b32 %0, [%1];" : "=r"(v) : "r"(a) : "memory"); return v; }
__device__ __forceinline__ uint32_t ldsv(uint32_t a) { uint32_t v; asm volatile("ld.volatile.shared.b32 %0, [%1];" : "=r"(v) : "r"(a) : "memory"); return v; }
__device__ __forceinline__ void stsv(uint32_t a, uint32_t v) { asm volatile("st.volatile.shared.b32 [%0], %1;" ::"r"(a), "r"(v) : "memory"); }
__device__ __forceinline__ float ldsf(uint32_t a) { float v; asm volatile("ld.shared.f32 %0, [%1];" : "=f"(v) : "r"(a) : "memory"); return v; }
__device__ __forceinline__ uint4 lds128(uint32_t a) { uint4 v; asm volatile("ld.shared.v4.b32 {%0,%1,%2,%3}, [%4];" : "=r"(v.x), "=r"(v.y), "=r"(v.z), "=r"(v.w) : "r"(a) : "memory"); return v; }
__device__ __forceinline__ void sts16(uint32_t a, uint16_t v) { asm volatile("st.shared.b16 [%0], %1;" ::"r"(a), "h"(v) : "memory"); }
__device__ __forceinline__ void sts32(uint32_t a, uint32_t v) { asm volatile("st.shared.b32 [%0], %1;" ::"r"(a), "r"(v) : "memory"); }
__device__ __forceinline__ void stsf2(uint32_t a, float x, float y) { asm volatile("st.shared.v2.f32 [%0], {%1,%2};" ::"r"(a), "f"(x), "f"(y) : "memory"); }
__device__ __forceinline__ void sts128(uint32_t a, uint4 v) { asm volatile("st.shared.v4.b32 [%0], {%1,%2,%3,%4};" ::"r"(a), "r"(v.x), "r"(v.y), "r"(v.z), "r"(v.w) : "memory"); }
__device__ __forceinline__ uint16_t f2bf(float x) { return __bfloat16_as_ushort(__float2bfloat16_rn(x)); }
__device__ __forceinline__ float bfround(float x) { return __bfloat162float(__float2bfloat16_rn(x)); }
__device__ __forceinline__ uint32_t pack2(float lo, float hi) { uint32_t r; asm("cvt.rn.bf16x2.f32 %0, %1, %2;" : "=r"(r) : "f"(hi), "f"(lo)); return r; }
__device__ __forceinline__ float ex2(float x) { float r; asm("ex2.approx.ftz.f32 %0, %1;" : "=f"(r) : "f"(x)); return r; }
__device__ __forceinline__ float lg2(float x) { float r; asm("lg2.approx.ftz.f32 %0, %1;" : "=f"(r) : "f"(x)); return r; }

__device__ __forceinline__ float rcp(float x) { float r; asm("rcp.approx.ftz.f32 %0, %1;" : "=f"(r) : "f"(x)); return r; }

__device__ __forceinline__ void sleep_ns(uint32_t ns) {
    uint32_t t0, t;
    asm volatile("mov.u32 %0, %clock;" : "=r"(t0));
    do { __nanosleep(200); asm volatile("mov.u32 %0, %clock;" : "=r"(t)); } while (t - t0 < 2 * ns);
}

__device__ __forceinline__ void ll_store2(ulonglong2* p, float a, float b, uint32_t tag) {
    unsigned long long x = ((unsigned long long)tag << 32) | __float_as_uint(a);
    unsigned long long y = ((unsigned long long)tag << 32) | __float_as_uint(b);
    asm volatile("st.relaxed.gpu.global.v2.b64 [%0], {%1,%2};" ::"l"(p), "l"(x), "l"(y) : "memory");
}
__device__ __forceinline__ void ll_ld2(const void* p, unsigned long long& x, unsigned long long& y) {
    asm volatile("ld.relaxed.gpu.global.v2.b64 {%0,%1}, [%2];" : "=l"(x), "=l"(y) : "l"(p) : "memory");
}
__device__ __forceinline__ void ll_gather4(const ulonglong2* p, uint32_t tag, float& r0, float& r1) {
    unsigned long long x[4], y[4]; uint32_t it = 0;
    while (true) {
        bool ok = true;
#pragma unroll
        for (int k = 0; k < 4; k++) ll_ld2(p + k * 128, x[k], y[k]);
#pragma unroll
        for (int k = 0; k < 4; k++) ok = ok && (uint32_t)(x[k] >> 32) == tag && (uint32_t)(y[k] >> 32) == tag;
        if (ok) break;
        if (++it > SPIN_MAX) __trap();
        __nanosleep(BACKOFF);
    }
    r0 = (__uint_as_float((uint32_t)x[0]) + __uint_as_float((uint32_t)x[1])) + (__uint_as_float((uint32_t)x[2]) + __uint_as_float((uint32_t)x[3]));
    r1 = (__uint_as_float((uint32_t)y[0]) + __uint_as_float((uint32_t)y[1])) + (__uint_as_float((uint32_t)y[2]) + __uint_as_float((uint32_t)y[3]));
}
__device__ __forceinline__ void cnt_rendezvous(unsigned* c, uint32_t target, int tsk) {
    TS(tsk);
    asm volatile("red.release.gpu.global.add.u32 [%0], 1;" ::"l"(c) : "memory");
    if (tsk == 18) TS(tsk + 1);
    uint32_t v, it = 0;
    while (true) {
        asm volatile("ld.acquire.gpu.global.u32 %0, [%1];" : "=r"(v) : "l"(c) : "memory");
        if ((int)(v - target) >= 0) break;
        if (++it > SPIN_MAX) __trap();
        __nanosleep(BACKOFF_RV);
    }
    asm volatile("fence.proxy.async.global;" ::: "memory");
}

__device__ __forceinline__ void matvec_loadA(uint32_t (&a)[8][4], uint32_t tile, uint32_t bar, int w, int lane) {
    const int i = lane >> 3, rr = lane & 7, chunk = 2 * w + (i & 1);
    const uint32_t a0 = tile + (chunk >> 3) * 8192 + (rr + 8 * (i >> 1)) * 128 + (((chunk & 7) ^ rr) << 4);
#pragma unroll
    for (int hh = 0; hh < 2; hh++) {
        mbar_wait(bar + hh * 8, 0);
#pragma unroll
        for (int k = 0; k < 4; k++) ldsm4t(a[hh * 4 + k], a0 + hh * CH + k * 2048);
    }
}
__device__ __forceinline__ void matvec_mma(float (&c)[4], const uint32_t (&a)[8][4], uint32_t vec, int nvec, int lane) {
    const uint32_t va = vec + (lane & (nvec - 1)) * VROW + (lane >> 3) * 16;
    float d[4][4];
#pragma unroll
    for (int q = 0; q < 4; q++) {
        uint32_t b[4];
        ldsm4(b, va + q * 64);
        d[q][0] = d[q][1] = d[q][2] = d[q][3] = 0.f;
        mma(d[q], a[2 * q], b[0], b[1]);
        mma(d[q], a[2 * q + 1], b[2], b[3]);
    }
#pragma unroll
    for (int k = 0; k < 4; k++) c[k] = (d[0][k] + d[1][k]) + (d[2][k] + d[3][k]);
}
__device__ __forceinline__ void matvecT(float (&c)[4], uint32_t tile, uint32_t vec, int nvec, uint32_t bar, int w, int lane) {
    uint32_t a[8][4];
    matvec_loadA(a, tile, bar, w, lane);
    matvec_mma(c, a, vec, nvec, lane);
}
template <class T> __device__ __forceinline__ T* pin(T* p) { asm volatile("" : "+l"(p)); return p; }
__device__ __forceinline__ void post(uint32_t* p, float v) {
    asm volatile("red.relaxed.gpu.global.add.u32 [%0], %1;" ::"l"(p), "r"(~__float_as_uint(v)) : "memory");
}
__device__ __forceinline__ void ld4_if(const void* p, uint4& x, bool need) {
    asm volatile("{\n.reg .pred q;\nsetp.ne.u32 q, %5, 0;\n@q ld.relaxed.gpu.global.v4.b32 {%0,%1,%2,%3}, [%4];\n}"
                 : "+r"(x.x), "+r"(x.y), "+r"(x.z), "+r"(x.w) : "l"(p), "r"((uint32_t)need) : "memory");
}
__device__ __forceinline__ void merge_store(const uint4 (&x)[5], uint32_t dst) {
#pragma unroll
    for (int b = 0; b < 2; b++) {
        const float l0 = __uint_as_float(~(b ? x[4].z : x[4].x)), l1 = __uint_as_float(~(b ? x[4].w : x[4].y));
        const float mx = fmaxf(l0, l1), e0 = ex2(l0 - mx), e1 = ex2(l1 - mx), r = rcp(e0 + e1);
        const uint4 u = x[2 * b], v = x[2 * b + 1];
        const uint32_t lo = pack2((e0 * __uint_as_float(~u.x) + e1 * __uint_as_float(~v.x)) * r, (e0 * __uint_as_float(~u.y) + e1 * __uint_as_float(~v.y)) * r);
        const uint32_t hi = pack2((e0 * __uint_as_float(~u.z) + e1 * __uint_as_float(~v.z)) * r, (e0 * __uint_as_float(~u.w) + e1 * __uint_as_float(~v.w)) * r);
        asm volatile("st.shared.v2.b32 [%0], {%1,%2};" ::"r"(dst + b * YROW), "r"(lo), "r"(hi) : "memory");
    }
}

__global__ void __launch_bounds__(NTHREADS, 1)
fused_decode_kernel(const char* __restrict__ wqraw, unsigned* const cnt, const __grid_constant__ Maps maps, const char* __restrict__ Kc, const char* __restrict__ Vc,
                    const __nv_bfloat16* __restrict__ xA, const __nv_bfloat16* __restrict__ xB,
                    __nv_bfloat16* __restrict__ out, const uint32_t zero) {
    asm volatile("{\n.reg .pred p;\nsetp.eq.u32 p, %1, 0;\n@p cp.async.bulk.prefetch.L2.global [%0], %2;\n}"
                 ::"l"(wqraw + (size_t)blockIdx.x * (2 * CH)), "r"(threadIdx.x), "n"(CH) : "memory");
    unsigned epoch = 0;
    asm volatile("{\n.reg .pred p;\nsetp.eq.u32 p, %2, 64;\n@p atom.relaxed.gpu.global.add.u32 %0, [%1], 1;\n}"
                 : "+r"(epoch) : "l"(cnt), "r"(threadIdx.x) : "memory");
    extern __shared__ char smem_raw[];
    const uint32_t sm = ((uint32_t)__cvta_generic_to_shared(smem_raw) + 1023u) & ~1023u;
    const uint32_t bars = sm + OFF_BAR;
    const int cta = blockIdx.x, h = cta >> 2, j = cta & 3;
    uint64_t pol = 0;
    if (threadIdx.x == 0) {
        TS(0);
        asm volatile("createpolicy.fractional.L2::evict_first.b64 %0, 1.0;" : "=l"(pol));
#pragma unroll
        for (int i = 0; i < WIN; i++) mbar_init(bars + (B_WQB + i) * 8, 1);
        asm volatile("fence.mbarrier_init.release.cluster;" ::: "memory");
#pragma unroll
        for (int i = 0; i < WIN; i++) {
            mbar_expect(bars + (B_WQB + i) * 8, CH);
            tma3d(sm + OFF_S0 + i * CH, &maps.wqB + (i >> 1), j * 128 + (i & 1) * 64, h * 2, bars + (B_WQB + i) * 8, pol);
        }
    }
    const int tid = threadIdx.x < 64 ? threadIdx.x + 384 : threadIdx.x - 64, warp = tid >> 5, lane = tid & 31;

    if (warp == 12) {
        const size_t kvoff = ((size_t)(((j >> 1) * 32 + h) * 4096 + (j & 1) * 2048)) * 256;
        const char* kp = Kc + kvoff;
        const char* vp = Vc + kvoff;
        __syncwarp();
        bar_arrive(0, NTHREADS);
        bar_sync(3, 64);
        if (lane == 0) {
            uint32_t pb[WHI];
#pragma unroll
            for (int i = 0; i < WHI; i++) pb[i] = i < WHI - WIN ? (bars + B_WO * 8) | 1u : bars + (B_WQB + i - (WHI - WIN)) * 8;
            auto pace = [&](uint32_t bar, uint32_t par, uint32_t wina) {
                uint32_t it = 0;
                while (true) {
                    const uint32_t win = ldsv(wina);
                    uint32_t busy = 0;
#pragma unroll
                    for (int i = 0; i < WHI; i++) busy += mbar_test(pb[i] & ~1u, pb[i] & 1u) ^ 1u;
                    if (busy < win) break;
                    if (++it > SPIN_MAX) __trap();
                }
#pragma unroll
                for (int i = 0; i + 1 < WHI; i++) pb[i] = pb[i + 1];
                pb[WHI - 1] = bar | par;
            };
            auto side = [&](const CUtensorMap* m, uint32_t dst, int bidx, int c1, int c2, uint32_t wina) {
                const uint32_t bar = bars + bidx * 8;
                pace(bar, 0, wina);
                mbar_expect(bar, CH);
                tma3d(dst, m, c1, c2, bar, pol);
            };
#pragma unroll 1
            for (int i = WIN; i < 6; i++)
                side(&maps.wqB + (i >> 1), sm + OFF_S0 + i * CH, B_WQB + i, j * 128 + (i & 1) * 64, h * 2, sm + OFF_WIN);
            TS(1);
            uint32_t slot = 0, use = 0;
            int nuv = 0;
#pragma unroll 1
            for (int n = 0; n < 2 * NTILE; n++) {
                if (n == RING) {
                    mbar_wait(bars + B_FREE * 8, 0);
#pragma unroll 1
                    for (int q = 0; q < 4; q++) side(&maps.ckv, sm + OFF_S0 + q * CH, B_CKV + q, cta * 64 + q * 16, 0, sm + OFF_WIN);
                }
                if (nuv < 2 && n > RING && (n >= 2 * NTILE - 8 || mbar_test(bars + B_FREE * 8, 1))) {
                    mbar_wait(bars + B_FREE * 8, 1);
                    side(&maps.wuv, sm + OFF_S1 + nuv * CH, B_WUV + nuv, j * 128 + nuv * 64, h * 2, sm + OFF_WIN);
                    nuv++;
                }
                const uint32_t fb = bars + slot * 8;
                pace(fb, use & 1, sm + OFF_WIN);
                mbar_wait(fb + B_EMPTY * 8, (use & 1) ^ 1);
                mbar_expect(fb, CH);
                bulk1d(sm + OFF_RING + slot * CH, ((n & 1) ? vp : kp) + (size_t)(n >> 1) * CH, fb, pol);
                if (n >= FINE_V || (n & 1)) {
                    asm volatile("red.relaxed.gpu.global.add.u32 [%0], %1;" ::"l"(cnt + 3), "r"(n >= FINE_V ? 1 : 2) : "memory");
                    stsv(sm + OFF_NOW, n + 1);
                }
                if (++slot == RING) { slot = 0; use++; }
            }
            TS(2);
            mbar_wait(bars + B_FREE * 8, 0);
            constexpr int NTB = WHI + 1;
            uint32_t tb[NTB];
#pragma unroll
            for (int i = 0; i < NTB; i++) tb[i] = i < NTB - WHI ? bars + B_WQB * 8 : pb[i - (NTB - WHI)] | 2u;
            uint32_t it = 0;
#pragma unroll 1
            for (int q = 0; q < 8;) {
                const uint32_t win = ldsv(sm + OFF_TWIN);
                uint32_t busy = 0;
#pragma unroll
                for (int i = 0; i < NTB; i++) busy += (mbar_test(tb[i] & ~3u, tb[i] & 1u) ^ 1u) << (tb[i] >> 1 & 1u);
#pragma unroll 1
                for (; busy < win && q < 8; busy++, q++) {
                    const uint32_t bar = bars + (B_WO + q) * 8;
                    mbar_expect(bar, CH / 2);
                    tma3d(sm + OFF_S0 + q * (CH / 2), &maps.woA + (cta & 1), (cta >> 4) * 512 + q * 64, (cta >> 1) & 7, bar, pol);
#pragma unroll
                    for (int i = 0; i + 1 < NTB; i++) tb[i] = tb[i + 1];
                    tb[NTB - 1] = bar;
                }
                if (++it > SPIN_MAX) __trap();
            }
            TS(3);
        }
    } else if (warp == 13) {
        if (lane == 0) {
#pragma unroll
            for (int i = 0; i < NBAR; i++)
                if (i < B_WQB || i >= B_WQB + WIN)
                    mbar_init(bars + i * 8, i == B_FREE ? 8 : (i >= B_EMPTY && i < B_EMPTY + RING) ? 4 : 1);
            asm volatile("fence.mbarrier_init.release.cluster;" ::: "memory");
#pragma unroll
            for (int i = 2; i < 8; i++) asm volatile("prefetch.tensormap [%0];" ::"l"(&maps.wqB + i) : "memory");
            stsv(sm + OFF_NOW, 0); stsv(sm + OFF_WIN, WIN); stsv(sm + OFF_TWIN, PREWIN);
        }
        __syncwarp();
        bar_arrive(3, 64);
        bar_sync(0, NTHREADS);
        if (lane == 0) {
            const uint32_t base = (lds32(sm + OFF_TAG) - 1u) * (NCTA * 2 * NTILE);
            mbar_wait(bars + (B_WUK + 1) * 8, 0);
            uint32_t it = 0;
            while (true) {
                const uint32_t n = ldsv(sm + OFF_NOW);
                uint32_t v;
                asm volatile("ld.relaxed.gpu.global.u32 %0, [%1];" : "=r"(v) : "l"(cnt + 3) : "memory");
                v -= base;
                if (v >= NCTA * 2 * NTILE - GATE_W) break;
                const int diff = (int)(n * NCTA) - (int)v;
                stsv(sm + OFF_WIN, diff < -THETA ? WHI : WIN - (diff > THETA) - (v >= NCTA * END_V));
                if (++it > SPIN_MAX) __trap();
                __nanosleep(v < NCTA * FINE_V ? BACKOFF3 : BACKOFF2);
            }
            stsv(sm + OFF_WIN, WHI); stsv(sm + OFF_TWIN, TAILWIN);
            TS(24);
        }
    } else if (warp < 4) {
        const int g = lane >> 2, t = lane & 3, i = lane >> 3, rr = lane & 7;
        if (tid == 0) sts32(sm + OFF_TAG, (epoch >> 7) + 1u);
        bar_sync(0, NTHREADS);
        const uint32_t tag = lds32(sm + OFF_TAG);
        {
            mbar_wait(bars + 8, 0);
            float q0, q1;
            ll_gather4(&g_e1[0][h * 4][tid], tag, q0, q1);
            sts16(sm + OFF_QB + tid * 2, f2bf((j >> 1) ? q1 : q0));
        }
        bar_sync(1, 128);
        if (tid == 0) TS(4);
        uint32_t qf[8][2];
#pragma unroll
        for (int c = 0; c < 8; c++) {
            const uint32_t a = sm + OFF_QB + (((c + g) & 7) * 8 + 2 * t) * 2;
            qf[c][0] = lds32(a); qf[c][1] = lds32(a + 128);
        }
        float acc[8][4];
#pragma unroll
        for (int c = 0; c < 8; c++) { acc[c][0] = acc[c][1] = acc[c][2] = acc[c][3] = 0.f; }
        float m = -INFINITY, l = 0.f;
        const bool diag = (t == (g >> 1));
        const uint32_t krow = sm + OFF_RING + (warp * 16 + rr + 8 * (i & 1)) * 256 + (i >> 1) * 128;
        const uint32_t vrow = sm + OFF_RING + (warp * 16 + rr + 8 * (i >> 1)) * 256 + (i & 1) * 128;
        uint32_t slot = 0, ph = 0;
        uint32_t* const e5own = pin(&g_e5[cta][tid]);
        uint32_t a[8][4], b0, b1;
#pragma unroll 1
        for (int tile = 0;; tile++) {
            mbar_wait(bars + slot * 8, ph);
#pragma unroll
            for (int c = 0; c < 8; c++) ldsm4(a[c], krow + slot * CH + (((c + rr) & 7) << 4));
            __syncwarp();
            if (lane == 0) mbar_arrive(bars + (B_EMPTY + slot) * 8 + ((a[0][0] | a[1][0] | a[2][0] | a[3][0] | a[4][0] | a[5][0] | a[6][0] | a[7][0]) & zero));
            if (++slot == RING) { slot = 0; ph ^= 1; }
            float s0[4] = {0.f, 0.f, 0.f, 0.f}, s1[4] = {0.f, 0.f, 0.f, 0.f};
#pragma unroll
            for (int c = 0; c < 8; c += 2) { mma(s0, a[c], qf[c][0], qf[c][1]); mma(s1, a[c + 1], qf[c + 1][0], qf[c + 1][1]); }
            float slo = (g & 1) ? s0[1] + s1[1] : s0[0] + s1[0];
            float shi = (g & 1) ? s0[3] + s1[3] : s0[2] + s1[2];
            slo = diag ? bfround(bfround(slo) * SCALE) : -INFINITY;
            shi = diag ? bfround(bfround(shi) * SCALE) : -INFINITY;
            int key = __float_as_int(fmaxf(slo, shi));
            key ^= (key >> 31) & 0x7fffffff;
            key = __reduce_max_sync(0xffffffffu, key);
            key ^= (key >> 31) & 0x7fffffff;
            const float mn = fmaxf(m, __int_as_float(key));
            const float alpha = ex2((m - mn) * LOG2E);
            m = mn;
            const float plo = ex2((slo - mn) * LOG2E), phi = ex2((shi - mn) * LOG2E);
            l = l * alpha + (plo + phi);
            b0 = (g & 1) ? pack2(0.f, plo) : pack2(plo, 0.f);
            b1 = (g & 1) ? pack2(0.f, phi) : pack2(phi, 0.f);
#pragma unroll
            for (int c = 0; c < 8; c++) { acc[c][0] *= alpha; acc[c][1] *= alpha; acc[c][2] *= alpha; acc[c][3] *= alpha; }
            if (tile == NTILE - 1) break;
            mbar_wait(bars + slot * 8, ph);
#pragma unroll
            for (int c = 0; c < 8; c++) ldsm4t(a[c], vrow + slot * CH + (((c + rr) & 7) << 4));
            __syncwarp();
            if (lane == 0) mbar_arrive(bars + (B_EMPTY + slot) * 8 + ((a[0][0] | a[1][0] | a[2][0] | a[3][0] | a[4][0] | a[5][0] | a[6][0] | a[7][0]) & zero));
            if (++slot == RING) { slot = 0; ph ^= 1; }
#pragma unroll
            for (int c = 0; c < 8; c++) mma(acc[c], a[c], b0, b1);
        }
#pragma unroll
        for (int o = 16; o; o >>= 1) l += __shfl_xor_sync(0xffffffffu, l, o);
        if (lane == 0) stsf2(sm + OFF_ML + warp * 8, m, l);
        mbar_wait(bars + B_S2 * 8, 0);
        bar_sync(1, 128);
        {
            const uint4 ml0 = lds128(sm + OFF_ML), ml1 = lds128(sm + OFF_ML + 16);
            const float m0 = __uint_as_float(ml0.x), m1 = __uint_as_float(ml0.z), m2 = __uint_as_float(ml1.x), m3 = __uint_as_float(ml1.z);
            const float M = fmaxf(fmaxf(m0, m1), fmaxf(m2, m3));
            const float L = (ex2((m0 - M) * LOG2E) * __uint_as_float(ml0.y) + ex2((m1 - M) * LOG2E) * __uint_as_float(ml0.w))
                          + (ex2((m2 - M) * LOG2E) * __uint_as_float(ml1.y) + ex2((m3 - M) * LOG2E) * __uint_as_float(ml1.w));
            const float f = ex2((m - M) * LOG2E) * rcp(L);
            if (tid == 0) post(e5own + (NCTA - cta) * 128 + cta, M * LOG2E + lg2(L));
            mbar_wait(bars + slot * 8, ph);
#pragma unroll
            for (int c = 0; c < 8; c++) ldsm4t(a[c], vrow + slot * CH + (((c + rr) & 7) << 4));
#pragma unroll
            for (int c = 0; c < 8; c++) mma(acc[c], a[c], b0, b1);
            if (tid == 0) TS(5);
            float v[2][8];
#pragma unroll
            for (int c = 0; c < 8; c++) { v[0][c] = acc[c][0] + acc[(c + 7) & 7][1]; v[1][c] = acc[c][2] + acc[(c + 7) & 7][3]; }
#pragma unroll
            for (int c = 0; c < 4; c++) { v[0][c] += __shfl_xor_sync(0xffffffffu, v[0][c + 4], 2); v[1][c] += __shfl_xor_sync(0xffffffffu, v[1][c + 4], 2); }
            const int src = (lane & ~3) | ((lane + 3) & 3);
#pragma unroll
            for (int c = 0; c < 2; c++) { v[0][c] += __shfl_sync(0xffffffffu, v[0][c + 2], src); v[1][c] += __shfl_sync(0xffffffffu, v[1][c + 2], src); }
            const uint32_t wa = sm + OFF_S2 + (warp * 160 + 16 * t + 8 * (t >> 1) + g) * 4;
            sts32(wa, __float_as_uint(v[0][0] * f)); sts32(wa + 32, __float_as_uint(v[0][1] * f));
            sts32(wa + 320, __float_as_uint(v[1][0] * f)); sts32(wa + 352, __float_as_uint(v[1][1] * f));
            bar_sync(1, 128);
            const uint32_t ra = sm + OFF_S2 + (tid + warp * 8) * 4;
            post(e5own, (ldsf(ra) + ldsf(ra + 640)) + (ldsf(ra + 1280) + ldsf(ra + 1920)));
        }
        if (tid == 0) TS(6);
        if (cta & 1) {
            const int c0 = (cta & ~15) + warp * 4;
            const uint32_t* p = e5own + ((c0 - cta) * 128 + lane * 4 - tid);
            const uint32_t* pl = e5own + ((NCTA - cta) * 128 + c0 - tid);
            uint4 x[5];
            bool need[5] = {true, true, true, true, true};
            uint32_t it = 0;
            while (true) {
#pragma unroll
                for (int q = 0; q < 5; q++) ld4_if(q < 4 ? p + q * 128 : pl, x[q], need[q]);
#pragma unroll
                for (int q = 0; q < 5; q++) need[q] = !x[q].x || !x[q].y || !x[q].z || !x[q].w;
                if (!__any_sync(0xffffffffu, need[0] | need[1] | need[2] | need[3] | need[4])) break;
                if (++it > SPIN_MAX) __trap();
            }
            merge_store(x, sm + OFF_Y + warp * YHEAD + lane * 8);
            bar_arrive(4, 256 + 128);
        }
        if (tid == 0) TS(16);
    } else {
        const int st = tid - 128, w = warp - 4;
        const int g = lane >> 2, t = lane & 3, i = lane >> 3, rr = lane & 7;
        if (t == 0) {
#pragma unroll
            for (int k = 0; k < 4; k++) ll_store2(&g_e1[k >> 1][cta][w * 16 + g + (k & 1) * 8], 0.f, 0.f, 0u);
        }
        if (st < 64) {
            const int which = st >> 5, b = (st >> 4) & 1, c = st & 15;
            const uint4 v = __ldg((const uint4*)((which ? xA : xB) + b * 512 + j * 128) + c);
            sts128(sm + OFF_XB + (which * 2 + b) * VROW + c * 16, v);
        }
        bar_sync(0, NTHREADS);
        const uint32_t tag = lds32(sm + OFF_TAG);
        float c[4];
#pragma unroll 1
        for (int which = 0; which < 2; which++) {
            matvecT(c, sm + OFF_S0 + which * 2 * CH, sm + OFF_XB + which * 2 * VROW, 2, bars + (B_WQB + which * 2) * 8, w, lane);
            if (t == 0) {
                ll_store2(&g_e1[which][cta][w * 16 + g], c[0], c[1], tag);
                ll_store2(&g_e1[which][cta][w * 16 + g + 8], c[2], c[3], tag);
            }
        }
        __syncwarp();
        if (lane == 0) mbar_arrive(bars + B_FREE * 8);
        if (st == 0) TS(8);
        if (st < 128) {
            float q0, q1;
            sleep_ns(POLL_DELAY);
            ll_gather4(&g_e1[1][h * 4][st], tag, q0, q1);
            sts16(sm + OFF_QA + st * 2, f2bf(q0)); sts16(sm + OFF_QA + VROW + st * 2, f2bf(q1));
        }
        bar_sync(2, 256);
        if (st == 0) TS(9);
        {
            const int row = w * 16 + rr + 8 * (i & 1);
            const uint32_t a0 = sm + OFF_S2 + (row >> 6) * CH + (row & 63) * 128;
            const uint32_t va = sm + OFF_QA + g * VROW + t * 4;
            float d[4] = {0.f, 0.f, 0.f, 0.f};
            c[0] = c[1] = c[2] = c[3] = 0.f;
            mbar_wait(bars + (B_WUK + (w >> 2)) * 8, 0);
#pragma unroll
            for (int ks = 0; ks < 8; ks++) {
                const int chunk = 2 * ks + (i >> 1);
                uint32_t a[4];
                ldsm4(a, a0 + (chunk >> 3) * 8192 + (((chunk & 7) ^ rr) << 4));
                const uint32_t b0 = (g < 2) ? lds32(va + ks * 32) : 0u, b1 = (g < 2) ? lds32(va + ks * 32 + 16) : 0u;
                if (ks & 1) mma(d, a, b0, b1); else mma(c, a, b0, b1);
            }
            if (t == 0) {
                const uint32_t qs = sm + OFF_QS + (w * 16 + g) * 2;
                sts16(qs, f2bf(c[0] + d[0])); sts16(qs + VROW, f2bf(c[1] + d[1]));
                sts16(qs + 16, f2bf(c[2] + d[2])); sts16(qs + VROW + 16, f2bf(c[3] + d[3]));
            }
            bar_sync(2, 256);
            if (w == 0) {
                const int b = lane >> 4, cc = lane & 15;
                g_qabs[(b * 32 + h) * 64 + ((j * 16 + cc) ^ (h & 7))] = lds128(sm + OFF_QS + b * VROW + cc * 16);
                __syncwarp();
                if (lane == 0) {
                    cnt_rendezvous(cnt + 1, tag * 128u, 18);
                    TS(10);
                    mbar_expect(bars + B_GATH * 8, 2 * CH);
                    bulk1d_n(sm + OFF_S2, g_qabs + (cta >> 6) * 2048, 2 * CH, bars + B_GATH * 8);
                }
                __syncwarp();
            }
        }
        mbar_wait(bars + B_GATH * 8, 0);
        if (st == 0) TS(11);
        {
            const int mt = w & 1, kg = w >> 1;
            const uint32_t qa = sm + OFF_S2 + (mt * 16 + rr + 8 * (i & 1)) * 1024;
            const uint32_t ka = sm + OFF_S0 + kg * CH + (rr + 8 * (i >> 1)) * 128;
            float s0[4] = {0.f, 0.f, 0.f, 0.f}, s1[4] = {0.f, 0.f, 0.f, 0.f};
            mbar_wait(bars + (B_CKV + kg) * 8, 0);
#pragma unroll 2
            for (int gq = 0; gq < 8; gq++) {
#pragma unroll
                for (int k4 = 0; k4 < 4; k4++) {
                    uint32_t a[4], b[4];
                    ldsm4(a, qa + gq * 128 + (((2 * k4 + (i >> 1)) ^ rr) << 4));
                    ldsm4(b, ka + gq * 2048 + (((2 * k4 + (i & 1)) ^ rr) << 4));
                    mma(s0, a, b[0], b[1]);
                    mma(s1, a, b[2], b[3]);
                }
            }
            const uint32_t sa = sm + OFF_SC + ((mt * 16 + g) * 68 + kg * 16 + 2 * t) * 4;
            stsf2(sa, s0[0], s0[1]); stsf2(sa + 32, s1[0], s1[1]);
            stsf2(sa + 8 * 68 * 4, s0[2], s0[3]); stsf2(sa + 8 * 68 * 4 + 32, s1[2], s1[3]);
        }
        bar_sync(2, 256);
        {
            const int head = w * 4 + i;
            const uint32_t sa = sm + OFF_SC + (head * 68 + rr * 8) * 4;
            const uint4 u0 = lds128(sa), u1 = lds128(sa + 16);
            float s[8] = {__uint_as_float(u0.x), __uint_as_float(u0.y), __uint_as_float(u0.z), __uint_as_float(u0.w),
                          __uint_as_float(u1.x), __uint_as_float(u1.y), __uint_as_float(u1.z), __uint_as_float(u1.w)};
            float mx = s[0];
#pragma unroll
            for (int k = 1; k < 8; k++) mx = fmaxf(mx, s[k]);
#pragma unroll
            for (int o = 1; o < 8; o <<= 1) mx = fmaxf(mx, __shfl_xor_sync(0xffffffffu, mx, o));
            float sum = 0.f;
#pragma unroll
            for (int k = 0; k < 8; k++) { s[k] = ex2((s[k] - mx) * (SCALE * LOG2E)); sum += s[k]; }
#pragma unroll
            for (int o = 1; o < 8; o <<= 1) sum += __shfl_xor_sync(0xffffffffu, sum, o);
            const float inv = __fdividef(1.f, sum);
            uint4 p;
            p.x = pack2(s[0] * inv, s[1] * inv); p.y = pack2(s[2] * inv, s[3] * inv);
            p.z = pack2(s[4] * inv, s[5] * inv); p.w = pack2(s[6] * inv, s[7] * inv);
            sts128(sm + OFF_P + head * 128 + ((rr ^ (head & 7)) << 4), p);
            if (rr == 0) ((float*)g_lse)[head * 128 + cta] = mx * (SCALE * LOG2E) + lg2(sum);
        }
        bar_sync(2, 256);
        {
            float o[2][8][4];
#pragma unroll
            for (int mt = 0; mt < 2; mt++)
#pragma unroll
                for (int n = 0; n < 8; n++) { o[mt][n][0] = o[mt][n][1] = o[mt][n][2] = o[mt][n][3] = 0.f; }
            const uint32_t pa = sm + OFF_P + (rr + 8 * (i & 1)) * 128;
            const uint32_t va = sm + OFF_S0 + w * 2048 + (rr + 8 * (i & 1)) * 128;
#pragma unroll 1
            for (int kq = 0; kq < 4; kq++) {
                uint32_t a0[4], a1[4];
                ldsm4(a0, pa + (((2 * kq + (i >> 1)) ^ rr) << 4));
                ldsm4(a1, pa + 2048 + (((2 * kq + (i >> 1)) ^ rr) << 4));
#pragma unroll
                for (int n = 0; n < 8; n += 2) {
                    uint32_t b[4];
                    ldsm4t(b, va + kq * CH + (((n + (i >> 1)) ^ rr) << 4));
                    mma(o[0][n], a0, b[0], b[1]); mma(o[1][n], a1, b[0], b[1]);
                    mma(o[0][n + 1], a0, b[2], b[3]); mma(o[1][n + 1], a1, b[2], b[3]);
                }
            }
#pragma unroll
            for (int mt = 0; mt < 2; mt++)
#pragma unroll
                for (int hf = 0; hf < 2; hf++) {
                    const uint32_t dst = sm + OFF_S2 + (mt * 16 + hf * 8 + g) * 1024 + w * 128 + t * 16;
#pragma unroll
                    for (int nb = 0; nb < 2; nb++) {
                        uint4 v;
                        v.x = pack2(o[mt][nb * 4 + 0][hf * 2], o[mt][nb * 4 + 0][hf * 2 + 1]);
                        v.y = pack2(o[mt][nb * 4 + 1][hf * 2], o[mt][nb * 4 + 1][hf * 2 + 1]);
                        v.z = pack2(o[mt][nb * 4 + 2][hf * 2], o[mt][nb * 4 + 2][hf * 2 + 1]);
                        v.w = pack2(o[mt][nb * 4 + 3][hf * 2], o[mt][nb * 4 + 3][hf * 2 + 1]);
                        sts128(dst + nb * 64, v);
                    }
                }
            asm volatile("fence.proxy.async.shared::cta;" ::: "memory");
            __syncwarp();
            if (lane == 0) mbar_arrive(bars + B_FREE * 8);
            g_e4[cta][st] = 0u;
            if (st < 128) g_e5[cta][st] = 0u;
            else if (cta == 0) g_e5[NCTA][st - 128] = 0u;
            if (st >= 248) ((uint32_t*)out)[cta * 8 + st - 248] = 0u;
        }
        bar_sync(2, 256);
        if (st == 0) {
            TS(12);
#pragma unroll 1
            for (int k = 0; k < ST_SPLIT; k++) {
                asm volatile("cp.async.bulk.tensor.3d.global.shared::cta.bulk_group [%0, {%2,%3,%4}], [%1];"
                             ::"l"(&maps.ctxp), "r"(sm + OFF_S2 + k * (2 * CH / ST_SPLIT)), "r"(0), "r"(cta), "r"(k * (128 / ST_SPLIT)) : "memory");
                if (k + 1 < ST_SPLIT) __nanosleep(ST_GAP);
            }
            asm volatile("cp.async.bulk.commit_group;" ::: "memory");
            asm volatile("cp.async.bulk.wait_group 0;" ::: "memory");
            cnt_rendezvous(cnt + 2, tag * 128u, 20);
            TS(13);
            mbar_expect(bars + B_GATH * 8, 2 * CH + 512);
            bulk1d_n(sm + OFF_LSE, g_lse + h * 32, 512, bars + B_GATH * 8);
#pragma unroll 1
            for (int k = 0; k < ST_SPLIT; k++) {
                bulk1d_n(sm + OFF_S2 + k * (2 * CH / ST_SPLIT), g_ctxp + cta * 2048 + k * (2048 / ST_SPLIT), 2 * CH / ST_SPLIT, bars + B_GATH * 8);
                __nanosleep(LD_GAP);
            }
        }
        __syncwarp();
        {
            mbar_wait(bars + B_GATH * 8, 1);
            if (st == 0) TS(22);
            uint4 v[8];
#pragma unroll
            for (int k = 0; k < 8; k++) v[k] = lds128(sm + OFF_S2 + (k * 256 + st) * 16);
            float ls[4];
#pragma unroll
            for (int k = 0; k < 4; k++) ls[k] = ldsf(sm + OFF_LSE + (k * 32 + lane) * 4);
            float m0 = fmaxf(ls[0], ls[1]), m1 = fmaxf(ls[2], ls[3]);
#pragma unroll
            for (int o = 16; o; o >>= 1) { m0 = fmaxf(m0, __shfl_xor_sync(0xffffffffu, m0, o)); m1 = fmaxf(m1, __shfl_xor_sync(0xffffffffu, m1, o)); }
            ls[0] = ex2(ls[0] - m0); ls[1] = ex2(ls[1] - m0); ls[2] = ex2(ls[2] - m1); ls[3] = ex2(ls[3] - m1);
            float z0 = ls[0] + ls[1], z1 = ls[2] + ls[3];
#pragma unroll
            for (int o = 16; o; o >>= 1) { z0 += __shfl_xor_sync(0xffffffffu, z0, o); z1 += __shfl_xor_sync(0xffffffffu, z1, o); }
            z0 = __fdividef(1.f, z0); z1 = __fdividef(1.f, z1);
            ls[0] *= z0; ls[1] *= z0; ls[2] *= z1; ls[3] *= z1;
            float a[2][8];
#pragma unroll
            for (int e = 0; e < 8; e++) a[0][e] = a[1][e] = 0.f;
            const int rg = st >> 4;
#pragma unroll
            for (int k = 0; k < 8; k++) {
                const float wt = __shfl_sync(0xffffffffu, ls[k >> 1], rg + 16 * (k & 1));
                const uint32_t u[4] = {v[k].x, v[k].y, v[k].z, v[k].w};
#pragma unroll
                for (int e = 0; e < 4; e++) {
                    a[k >> 2][2 * e] += wt * __uint_as_float(u[e] << 16);
                    a[k >> 2][2 * e + 1] += wt * __uint_as_float(u[e] & 0xffff0000u);
                }
            }
            const int b = lane >> 4, u16 = lane & 15;
            const uint32_t ra = sm + OFF_SC + (w * 256 + b * 128 + (u16 >> 3) * 64 + ((u16 >> 2) & 1) * 32 + (u16 & 3) * 2) * 4;
#pragma unroll
            for (int e = 0; e < 8; e += 2) {
                const float k0 = b ? a[1][e] : a[0][e], k1 = b ? a[1][e + 1] : a[0][e + 1];
                const float s0 = b ? a[0][e] : a[1][e], s1 = b ? a[0][e + 1] : a[1][e + 1];
                stsf2(ra + (e >> 1) * 32, k0 + __shfl_xor_sync(0xffffffffu, s0, 16), k1 + __shfl_xor_sync(0xffffffffu, s1, 16));
            }
            bar_sync(2, 256);
            if (st == 0) mbar_arrive(bars + B_S2 * 8);
            float s = 0.f;
#pragma unroll
            for (int k = 0; k < 8; k++) s += ldsf(sm + OFF_SC + (k * 256 + st) * 4);
            const float hi = bfround(s);
            const uint32_t ca = sm + OFF_CC + (st >> 7) * VROW + (st & 127) * 2;
            sts16(ca, f2bf(hi)); sts16(ca + 2 * VROW, f2bf(s - hi));
            bar_sync(2, 256);
        }
        matvecT(c, sm + OFF_S1, sm + OFF_CC, 4, bars + B_WUV * 8, w, lane);
#pragma unroll
        for (int k = 0; k < 4; k++) c[k] += __shfl_xor_sync(0xffffffffu, c[k], 1);
        post(&g_e4[cta][(t & 1) * 128 + w * 16 + (t >> 1) * 8 + g], t == 0 ? c[0] : t == 1 ? c[1] : t == 2 ? c[2] : c[3]);
        __syncwarp();
        if (lane == 0) mbar_arrive(bars + B_FREE * 8);
        if (st == 0) TS(23);
        if (st < 128) sts32(sm + OFF_PAIR + st * 4, EMPTY);
        if (!(cta & 1)) {
            const uint32_t* p = &g_e4[(cta & ~15) + (w >> 1) * 4][(w & 1) * 128 + lane * 4];
            uint4 x[4];
            bool need[4] = {true, true, true, true};
            uint32_t it = 0;
            sleep_ns(POLL_DELAY2);
            while (true) {
#pragma unroll
                for (int q = 0; q < 4; q++) ld4_if(p + q * 256, x[q], need[q]);
#pragma unroll
                for (int q = 0; q < 4; q++) need[q] = !x[q].x || !x[q].y || !x[q].z || !x[q].w;
                if (!__any_sync(0xffffffffu, need[0] | need[1] | need[2] | need[3])) break;
                if (++it > SPIN_MAX) __trap();
                __nanosleep(BACKOFF);
            }
            auto sum4 = [](uint32_t a, uint32_t b, uint32_t c, uint32_t d) {
                return (__uint_as_float(~a) + __uint_as_float(~b)) + (__uint_as_float(~c) + __uint_as_float(~d));
            };
            asm volatile("st.shared.v2.b32 [%0], {%1,%2};" ::"r"(sm + OFF_Y + (w & 1) * YROW + (w >> 1) * YHEAD + lane * 8),
                         "r"(pack2(sum4(x[0].x, x[1].x, x[2].x, x[3].x), sum4(x[0].y, x[1].y, x[2].y, x[3].y))),
                         "r"(pack2(sum4(x[0].z, x[1].z, x[2].z, x[3].z), sum4(x[0].w, x[1].w, x[2].w, x[3].w))) : "memory");
        }
        if (st == 0) TS(14);
        bar_sync(2, 256);
        {
            const int hf = w >> 2, cg = w & 3;
            const uint32_t a0 = sm + OFF_S0 + hf * 8192 + (rr + 8 * (i >> 1)) * 128 + (((2 * cg + (i & 1)) ^ rr) << 4);
            const uint32_t va = sm + OFF_Y + (lane >> 1 & 1) * YROW + (lane & 1) * YHEAD + hf * 128 + i * 16;
            const uint32_t wb = bars + (B_WO + hf) * 8;
            const uint32_t pa = sm + OFF_PAIR + (cg * 32 + lane) * 4;
            const int col = (t & 1) * 1024 + (cta & 1) * 512 + (cta >> 1 & 7) * 64 + cg * 16 + (t >> 1) * 8 + g;
            __nv_bfloat16* const outp = pin(out + (col & ~1));
            const bool up = t >= 2, odd = g & 1;
            uint32_t a[4][4][4], b[4][4];
            float d[2][4][4];
#pragma unroll
            for (int k = 0; k < 8; k++) d[k >> 2][k & 3][0] = d[k >> 2][k & 3][1] = d[k >> 2][k & 3][2] = d[k >> 2][k & 3][3] = 0.f;
            auto load_w = [&](int hd) {
                mbar_wait(wb + hd * 16, 0);
#pragma unroll
                for (int k = 0; k < 4; k++) ldsm4t(a[hd][k], a0 + hd * CH + k * 2048);
            };
            auto load_y = [&]() {
#pragma unroll
                for (int q = 0; q < 4; q++) ldsm4(b[q], va + (q >> 1) * 2 * YHEAD + (q & 1) * 64);
            };
            auto head = [&](int hd) {
#pragma unroll
                for (int k = 0; k < 4; k++) mma(d[hd & 1][k], a[hd][k], b[(hd & 2) + (k >> 1)][(k & 1) * 2], b[(hd & 2) + (k >> 1)][(k & 1) * 2 + 1]);
            };
            if (cta & 1) {
                load_w(0); load_w(1);
                bar_sync(4, 256 + 128);
                load_y();
                head(0); head(1);
            } else {
                load_y();
                load_w(0); head(0);
                load_w(1); head(1);
            }
            if (st == 0) TS(25);
            load_w(2); head(2);
            float z = up ? (d[0][0][2] + d[0][1][2]) + (d[0][2][2] + d[0][3][2]) : (d[0][0][0] + d[0][1][0]) + (d[0][2][0] + d[0][3][0]);
            load_w(3);
            if (st == 0) TS(26);
            uint32_t other = ldsv(pa);
            head(3);
            z += other != EMPTY ? __uint_as_float(other) : 0.f;
            z = up ? ((z + d[1][0][3]) + d[1][1][3]) + (d[1][2][3] + d[1][3][3]) : ((z + d[1][0][1]) + d[1][1][1]) + (d[1][2][1] + d[1][3][1]);
            if (st == 0) TS(17);
            asm volatile("{\n.reg .pred p;\nsetp.ne.u32 p, %2, %3;\n@p red.relaxed.gpu.global.add.noftz.bf16x2 [%0], %1;\n@p exit;\n}"
                         ::"l"(outp), "r"(odd ? pack2(0.f, z) : pack2(z, 0.f)), "r"(other), "n"(EMPTY) : "memory");
            {
                asm volatile("atom.shared.exch.b32 %0, [%1], %2;" : "=r"(other) : "r"(pa), "r"(__float_as_uint(z)) : "memory");
                z += __uint_as_float(other);
            }
            if (other != EMPTY)
                asm volatile("red.relaxed.gpu.global.add.noftz.bf16x2 [%0], %1;" ::"l"(outp), "r"(odd ? pack2(0.f, z) : pack2(z, 0.f)) : "memory");
        }
    }
}

typedef CUresult (*EncodeFn)(CUtensorMap*, CUtensorMapDataType, cuuint32_t, void*, const cuuint64_t*, const cuuint64_t*,
                             const cuuint32_t*, const cuuint32_t*, CUtensorMapInterleave, CUtensorMapSwizzle,
                             CUtensorMapL2promotion, CUtensorMapFloatOOBfill);

void make_map(EncodeFn enc, CUtensorMap* m, void* p, unsigned rows, unsigned cols, unsigned br, unsigned bg) {
    cuuint64_t gd[3] = {64, rows, cols / 64};
    cuuint64_t gs[2] = {(cuuint64_t)cols * 2, 128};
    cuuint32_t bx[3] = {64, br, bg};
    cuuint32_t es[3] = {1, 1, 1};
    enc(m, CU_TENSOR_MAP_DATA_TYPE_BFLOAT16, 3, p, gd, gs, bx, es, CU_TENSOR_MAP_INTERLEAVE_NONE,
        CU_TENSOR_MAP_SWIZZLE_128B, CU_TENSOR_MAP_L2_PROMOTION_L2_128B, CU_TENSOR_MAP_FLOAT_OOB_FILL_NONE);
}

}

extern "C" void kernel_launch(void* const* d_in, const int* in_sizes, int n_in, void* d_out, int out_size) {
    static EncodeFn enc = nullptr;
    if (!enc) {
        void* fn = nullptr;
        cudaDriverEntryPointQueryResult qr;
        cudaGetDriverEntryPoint("cuTensorMapEncodeTiled", &fn, cudaEnableDefault, &qr);
        enc = (EncodeFn)fn;
        cudaFuncSetAttribute(fused_decode_kernel, cudaFuncAttributeMaxDynamicSharedMemorySize, SMEM_BYTES);
    }
    Maps maps;
    make_map(enc, &maps.wqB, d_in[9], 512, 4096, 64, 2);
    make_map(enc, &maps.wqA, d_in[2], 512, 4096, 64, 2);
    make_map(enc, &maps.wuk, d_in[3], 512, 4096, 64, 2);
    make_map(enc, &maps.wuv, d_in[4], 512, 4096, 64, 2);
    make_map(enc, &maps.woA, d_in[5], 4096, 512, 64, 1);
    make_map(enc, &maps.woB, d_in[10], 4096, 512, 64, 1);
    make_map(enc, &maps.ckv, d_in[1], 8192, 512, 16, 8);
    {
        void* p = nullptr;
        cudaGetSymbolAddress(&p, g_ctxp);
        cuuint64_t gd[3] = {128, 128, 128};
        cuuint64_t gs[2] = {256, 32768};
        cuuint32_t bx[3] = {128, 1, 128 / ST_SPLIT};
        cuuint32_t es[3] = {1, 1, 1};
        enc(&maps.ctxp, CU_TENSOR_MAP_DATA_TYPE_BFLOAT16, 3, p, gd, gs, bx, es, CU_TENSOR_MAP_INTERLEAVE_NONE,
            CU_TENSOR_MAP_SWIZZLE_NONE, CU_TENSOR_MAP_L2_PROMOTION_NONE, CU_TENSOR_MAP_FLOAT_OOB_FILL_NONE);
    }
    void* cnt = nullptr;
    cudaGetSymbolAddress(&cnt, g_cnt);
    fused_decode_kernel<<<NCTA, NTHREADS, SMEM_BYTES>>>((const char*)d_in[9], (unsigned*)cnt, maps, (const char*)d_in[7], (const char*)d_in[8],
                                                         (const __nv_bfloat16*)d_in[0], (const __nv_bfloat16*)d_in[6],
                                                         (__nv_bfloat16*)d_out, 0u);
}
```

```cpp
#include <cuda_runtime.h>
#include <cuda.h>
#include <cuda_bf16.h>
#include <stdint.h>

#define RING 7
#define WIN 4
#define WHI 5
#define THETA 64
#define END_V 40
#define GATE_W 64
#define BOX_NS 319
#define BOX_SHIFT -25
#define BOX_SPREAD 150
#define EST_FROM 57
#define EST_TO 62
#define POLL_DELAY 2500
#define POLL_DELAY2 2500
#define ST_SPLIT 8
#define ST_GAP 500
#define LD_GAP 300
#define BACKOFF 200
#define BACKOFF_RV 800
#define FINE_V 52
#define BACKOFF2 100
#define BACKOFF3 300

namespace {

constexpr int NCTA = 128;
constexpr int NTHREADS = 448;
constexpr uint32_t CH = 16384;
constexpr int NTILE = 32;

constexpr uint32_t OFF_RING = 0;
constexpr uint32_t OFF_S0 = RING * CH;
constexpr uint32_t OFF_S1 = OFF_S0 + 2 * CH;
constexpr uint32_t OFF_S2 = OFF_S1 + 2 * CH;
constexpr uint32_t OFF_P = OFF_S2 + 2 * CH;
constexpr uint32_t OFF_SC = OFF_P + 4096;
constexpr uint32_t VROW = 272;
constexpr uint32_t OFF_XB = OFF_SC + 8704;
constexpr uint32_t OFF_XA = OFF_XB + 2 * VROW;
constexpr uint32_t OFF_QA = OFF_XA + 2 * VROW;
constexpr uint32_t OFF_QS = OFF_QA + 2 * VROW;
constexpr uint32_t OFF_CC = OFF_QS + 2 * VROW;
constexpr uint32_t OFF_QB = OFF_CC + 4 * VROW;
constexpr uint32_t YHEAD = 288, YROW = 4 * YHEAD + 16;
constexpr uint32_t OFF_Y = OFF_P;
constexpr uint32_t OFF_PAIR = OFF_P + 2 * YROW;
constexpr uint32_t EMPTY = 0xffffffffu;
constexpr uint32_t OFF_LSE = OFF_QB + 256;
constexpr uint32_t OFF_ML = OFF_LSE + 512;
constexpr uint32_t OFF_TAG = OFF_ML + 32;
constexpr uint32_t OFF_NOW = OFF_TAG + 4;
constexpr uint32_t OFF_WIN = OFF_TAG + 8;
constexpr uint32_t OFF_TBOX = OFF_TAG + 12;
constexpr uint32_t OFF_BAR = OFF_TAG + 16;
constexpr int B_EMPTY = RING;
constexpr int B_WQB = 2 * RING;
constexpr int B_WQA = B_WQB + 2;
constexpr int B_WUK = B_WQA + 2;
constexpr int B_WUV = B_WUK + 2;
constexpr int B_CKV = B_WUV + 2;
constexpr int B_WO = B_CKV + 4;
constexpr int B_FREE = B_WO + 8;
constexpr int B_GATH = B_FREE + 1;
constexpr int B_S2 = B_GATH + 1;
constexpr int NBAR = B_S2 + 1;
constexpr uint32_t TS_OFF = OFF_BAR + NBAR * 8;
constexpr uint32_t SMEM_USED = TS_OFF;
constexpr uint32_t SMEM_BYTES = SMEM_USED + 1024;
static_assert(SMEM_BYTES <= 232448, "smem");
static_assert(RING >= WHI && WHI >= WIN && WIN >= 3 && WIN <= 6 && FINE_V % 2 == 0, "windows");

constexpr float LOG2E = 1.4426950408889634f;
constexpr float SCALE = 0.08838834764831845f;
#define SPIN_LOG 22
constexpr uint32_t SPIN_MAX = 1u << SPIN_LOG;

struct Maps { CUtensorMap wqB, wqA, wuk, wuv, woA, woB, ckv, ctxp; };

__device__ __align__(256) unsigned g_cnt[4];
__device__ __align__(256) ulonglong2 g_e1[2][NCTA][128];
__device__ __align__(256) uint4 g_qabs[2 * 32 * 64];
__device__ __align__(256) uint4 g_ctxp[NCTA * 128 * 16];
__device__ __align__(256) float4 g_lse[32 * 32];
__device__ __align__(256) uint32_t g_e4[NCTA][256];
__device__ __align__(256) uint32_t g_e5[NCTA + 1][128];

#define TS(k) do {} while (0)

__device__ __forceinline__ void mbar_init(uint32_t b, int c) { asm volatile("mbarrier.init.shared::cta.b64 [%0], %1;" ::"r"(b), "r"(c) : "memory"); }
__device__ __forceinline__ void mbar_expect(uint32_t b, uint32_t bytes) { asm volatile("mbarrier.arrive.expect_tx.shared::cta.b64 _, [%0], %1;" ::"r"(b), "r"(bytes) : "memory"); }
__device__ __forceinline__ void mbar_arrive(uint32_t b) { asm volatile("mbarrier.arrive.shared::cta.b64 _, [%0];" ::"r"(b) : "memory"); }
__device__ __forceinline__ void mbar_wait(uint32_t b, uint32_t ph) {
    uint32_t ok, it = 0;
    do {
        asm volatile("{\n.reg .pred p;\nmbarrier.try_wait.parity.shared::cta.b64 p, [%1], %2;\nselp.u32 %0, 1, 0, p;\n}" : "=r"(ok) : "r"(b), "r"(ph) : "memory");
        if (++it > SPIN_MAX) __trap();
    } while (!ok);
}
__device__ __forceinline__ void mbar_wait_uni(uint32_t b) {
    asm volatile("{\n.reg .pred p, q;\n.reg .u32 n;\nmov.u32 n, 0;\nAGAIN:\nadd.u32 n, n, 1;\nsetp.gt.u32 q, n, %1;\n"
                 "mbarrier.try_wait.parity.shared::cta.b64 p, [%0], 0;\n@q trap;\n@!p bra.uni AGAIN;\n}" ::"r"(b), "n"(SPIN_MAX) : "memory");
}
__device__ __forceinline__ uint32_t mbar_test(uint32_t b, uint32_t ph) {
    uint32_t ok;
    asm volatile("{\n.reg .pred p;\nmbarrier.test_wait.parity.shared::cta.b64 p, [%1], %2;\nselp.u32 %0, 1, 0, p;\n}" : "=r"(ok) : "r"(b), "r"(ph) : "memory");
    return ok;
}
__device__ __forceinline__ void bulk1d(uint32_t dst, const void* src, uint32_t bar, uint64_t pol) {
    asm volatile("cp.async.bulk.shared::cluster.global.mbarrier::complete_tx::bytes.L2::cache_hint [%0], [%1], %2, [%3], %4;"
                 ::"r"(dst), "l"(src), "n"(CH), "r"(bar), "l"(pol) : "memory");
}
__device__ __forceinline__ void bulk1d_n(uint32_t dst, const void* src, uint32_t bytes, uint32_t bar) {
    asm volatile("cp.async.bulk.shared::cluster.global.mbarrier::complete_tx::bytes [%0], [%1], %2, [%3];"
                 ::"r"(dst), "l"(src), "r"(bytes), "r"(bar) : "memory");
}
__device__ __forceinline__ void tma3d(uint32_t dst, const CUtensorMap* map, int c1, int c2, uint32_t bar, uint64_t pol) {
    asm volatile("cp.async.bulk.tensor.3d.shared::cluster.global.mbarrier::complete_tx::bytes.L2::cache_hint [%0], [%1, {%3,%4,%5}], [%2], %6;"
                 ::"r"(dst), "l"(map), "r"(bar), "r"(0), "r"(c1), "r"(c2), "l"(pol) : "memory");
}
__device__ __forceinline__ void bar_sync(int id, int n) { asm volatile("barrier.cta.sync %0, %1;" ::"r"(id), "r"(n) : "memory"); }
__device__ __forceinline__ void bar_arrive(int id, int n) { asm volatile("barrier.cta.arrive %0, %1;" ::"r"(id), "r"(n) : "memory"); }
__device__ __forceinline__ void ldsm4(uint32_t (&r)[4], uint32_t a) {
    asm volatile("ldmatrix.sync.aligned.m8n8.x4.shared.b16 {%0,%1,%2,%3}, [%4];" : "=r"(r[0]), "=r"(r[1]), "=r"(r[2]), "=r"(r[3]) : "r"(a) : "memory");
}
__device__ __forceinline__ void ldsm4t(uint32_t (&r)[4], uint32_t a) {
    asm volatile("ldmatrix.sync.aligned.m8n8.x4.trans.shared.b16 {%0,%1,%2,%3}, [%4];" : "=r"(r[0]), "=r"(r[1]), "=r"(r[2]), "=r"(r[3]) : "r"(a) : "memory");
}
__device__ __forceinline__ void mma(float (&c)[4], const uint32_t (&a)[4], uint32_t b0, uint32_t b1) {
    asm volatile("mma.sync.aligned.m16n8k16.row.col.f32.bf16.bf16.f32 {%0,%1,%2,%3}, {%4,%5,%6,%7}, {%8,%9}, {%0,%1,%2,%3};"
                 : "+f"(c[0]), "+f"(c[1]), "+f"(c[2]), "+f"(c[3]) : "r"(a[0]), "r"(a[1]), "r"(a[2]), "r"(a[3]), "r"(b0), "r"(b1));
}
__device__ __forceinline__ uint32_t lds32(uint32_t a) { uint32_t v; asm volatile("ld.shared.b32 %0, [%1];" : "=r"(v) : "r"(a) : "memory"); return v; }
__device__ __forceinline__ uint32_t ldsv(uint32_t a) { uint32_t v; asm volatile("ld.volatile.shared.b32 %0, [%1];" : "=r"(v) : "r"(a) : "memory"); return v; }
__device__ __forceinline__ void stsv(uint32_t a, uint32_t v) { asm volatile("st.volatile.shared.b32 [%0], %1;" ::"r"(a), "r"(v) : "memory"); }
__device__ __forceinline__ float ldsf(uint32_t a) { float v; asm volatile("ld.shared.f32 %0, [%1];" : "=f"(v) : "r"(a) : "memory"); return v; }
__device__ __forceinline__ uint4 lds128(uint32_t a) { uint4 v; asm volatile("ld.shared.v4.b32 {%0,%1,%2,%3}, [%4];" : "=r"(v.x), "=r"(v.y), "=r"(v.z), "=r"(v.w) : "r"(a) : "memory"); return v; }
__device__ __forceinline__ void sts16(uint32_t a, uint16_t v) { asm volatile("st.shared.b16 [%0], %1;" ::"r"(a), "h"(v) : "memory"); }
__device__ __forceinline__ void sts32(uint32_t a, uint32_t v) { asm volatile("st.shared.b32 [%0], %1;" ::"r"(a), "r"(v) : "memory"); }
__device__ __forceinline__ void stsf2(uint32_t a, float x, float y) { asm volatile("st.shared.v2.f32 [%0], {%1,%2};" ::"r"(a), "f"(x), "f"(y) : "memory"); }
__device__ __forceinline__ void sts128(uint32_t a, uint4 v) { asm volatile("st.shared.v4.b32 [%0], {%1,%2,%3,%4};" ::"r"(a), "r"(v.x), "r"(v.y), "r"(v.z), "r"(v.w) : "memory"); }
__device__ __forceinline__ uint16_t f2bf(float x) { return __bfloat16_as_ushort(__float2bfloat16_rn(x)); }
__device__ __forceinline__ float bfround(float x) { return __bfloat162float(__float2bfloat16_rn(x)); }
__device__ __forceinline__ uint32_t pack2(float lo, float hi) { uint32_t r; asm("cvt.rn.bf16x2.f32 %0, %1, %2;" : "=r"(r) : "f"(hi), "f"(lo)); return r; }
__device__ __forceinline__ float ex2(float x) { float r; asm("ex2.approx.ftz.f32 %0, %1;" : "=f"(r) : "f"(x)); return r; }
__device__ __forceinline__ float lg2(float x) { float r; asm("lg2.approx.ftz.f32 %0, %1;" : "=f"(r) : "f"(x)); return r; }

__device__ __forceinline__ float rcp(float x) { float r; asm("rcp.approx.ftz.f32 %0, %1;" : "=f"(r) : "f"(x)); return r; }

__device__ __forceinline__ uint32_t gtime() { uint32_t t; asm volatile("mov.u32 %0, %globaltimer_lo;" : "=r"(t)::"memory"); return t; }
__device__ __forceinline__ void sleep_ns(uint32_t ns) {
    uint32_t t0, t;
    asm volatile("mov.u32 %0, %clock;" : "=r"(t0));
    do { __nanosleep(200); asm volatile("mov.u32 %0, %clock;" : "=r"(t)); } while (t - t0 < 2 * ns);
}

__device__ __forceinline__ void ll_store2(ulonglong2* p, float a, float b, uint32_t tag) {
    unsigned long long x = ((unsigned long long)tag << 32) | __float_as_uint(a);
    unsigned long long y = ((unsigned long long)tag << 32) | __float_as_uint(b);
    asm volatile("st.relaxed.gpu.global.v2.b64 [%0], {%1,%2};" ::"l"(p), "l"(x), "l"(y) : "memory");
}
__device__ __forceinline__ void ll_ld2(const void* p, unsigned long long& x, unsigned long long& y) {
    asm volatile("ld.relaxed.gpu.global.v2.b64 {%0,%1}, [%2];" : "=l"(x), "=l"(y) : "l"(p) : "memory");
}
__device__ __forceinline__ void ll_gather4(const ulonglong2* p, uint32_t tag, float& r0, float& r1) {
    unsigned long long x[4], y[4]; uint32_t it = 0;
    while (true) {
        bool ok = true;
#pragma unroll
        for (int k = 0; k < 4; k++) ll_ld2(p + k * 128, x[k], y[k]);
#pragma unroll
        for (int k = 0; k < 4; k++) ok = ok && (uint32_t)(x[k] >> 32) == tag && (uint32_t)(y[k] >> 32) == tag;
        if (ok) break;
        if (++it > SPIN_MAX) __trap();
        __nanosleep(BACKOFF);
    }
    r0 = (__uint_as_float((uint32_t)x[0]) + __uint_as_float((uint32_t)x[1])) + (__uint_as_float((uint32_t)x[2]) + __uint_as_float((uint32_t)x[3]));
    r1 = (__uint_as_float((uint32_t)y[0]) + __uint_as_float((uint32_t)y[1])) + (__uint_as_float((uint32_t)y[2]) + __uint_as_float((uint32_t)y[3]));
}
__device__ __forceinline__ void cnt_rendezvous(unsigned* c, uint32_t target, int tsk) {
    TS(tsk);
    asm volatile("red.release.gpu.global.add.u32 [%0], 1;" ::"l"(c) : "memory");
    if (tsk == 18) TS(tsk + 1);
    uint32_t v, it = 0;
    while (true) {
        asm volatile("ld.acquire.gpu.global.u32 %0, [%1];" : "=r"(v) : "l"(c) : "memory");
        if ((int)(v - target) >= 0) break;
        if (++it > SPIN_MAX) __trap();
        __nanosleep(BACKOFF_RV);
    }
    asm volatile("fence.proxy.async.global;" ::: "memory");
}

__device__ __forceinline__ void matvec_loadA(uint32_t (&a)[8][4], uint32_t tile, uint32_t bar, int w, int lane) {
    const int i = lane >> 3, rr = lane & 7, chunk = 2 * w + (i & 1);
    const uint32_t a0 = tile + (chunk >> 3) * 8192 + (rr + 8 * (i >> 1)) * 128 + (((chunk & 7) ^ rr) << 4);
#pragma unroll
    for (int hh = 0; hh < 2; hh++) {
        mbar_wait(bar + hh * 8, 0);
#pragma unroll
        for (int k = 0; k < 4; k++) ldsm4t(a[hh * 4 + k], a0 + hh * CH + k * 2048);
    }
}
__device__ __forceinline__ void matvec_mma(float (&c)[4], const uint32_t (&a)[8][4], uint32_t vec, int nvec, int lane) {
    const uint32_t va = vec + (lane & (nvec - 1)) * VROW + (lane >> 3) * 16;
    float d[4][4];
#pragma unroll
    for (int q = 0; q < 4; q++) {
        uint32_t b[4];
        ldsm4(b, va + q * 64);
        d[q][0] = d[q][1] = d[q][2] = d[q][3] = 0.f;
        mma(d[q], a[2 * q], b[0], b[1]);
        mma(d[q], a[2 * q + 1], b[2], b[3]);
    }
#pragma unroll
    for (int k = 0; k < 4; k++) c[k] = (d[0][k] + d[1][k]) + (d[2][k] + d[3][k]);
}
__device__ __forceinline__ void matvecT(float (&c)[4], uint32_t tile, uint32_t vec, int nvec, uint32_t bar, int w, int lane) {
    uint32_t a[8][4];
    matvec_loadA(a, tile, bar, w, lane);
    matvec_mma(c, a, vec, nvec, lane);
}
template <class T> __device__ __forceinline__ T* pin(T* p) { asm volatile("" : "+l"(p)); return p; }
__device__ __forceinline__ void post(uint32_t* p, float v) {
    asm volatile("red.relaxed.gpu.global.add.u32 [%0], %1;" ::"l"(p), "r"(~__float_as_uint(v)) : "memory");
}
__device__ __forceinline__ void ld4_if(const void* p, uint4& x, bool need) {
    asm volatile("{\n.reg .pred q;\nsetp.ne.u32 q, %5, 0;\n@q ld.relaxed.gpu.global.v4.b32 {%0,%1,%2,%3}, [%4];\n}"
                 : "+r"(x.x), "+r"(x.y), "+r"(x.z), "+r"(x.w) : "l"(p), "r"((uint32_t)need) : "memory");
}
__device__ __forceinline__ void merge_store(const uint4 (&x)[5], uint32_t dst) {
#pragma unroll
    for (int b = 0; b < 2; b++) {
        const float l0 = __uint_as_float(~(b ? x[4].z : x[4].x)), l1 = __uint_as_float(~(b ? x[4].w : x[4].y));
        const float mx = fmaxf(l0, l1), e0 = ex2(l0 - mx), e1 = ex2(l1 - mx), r = rcp(e0 + e1);
        const uint4 u = x[2 * b], v = x[2 * b + 1];
        const uint32_t lo = pack2((e0 * __uint_as_float(~u.x) + e1 * __uint_as_float(~v.x)) * r, (e0 * __uint_as_float(~u.y) + e1 * __uint_as_float(~v.y)) * r);
        const uint32_t hi = pack2((e0 * __uint_as_float(~u.z) + e1 * __uint_as_float(~v.z)) * r, (e0 * __uint_as_float(~u.w) + e1 * __uint_as_float(~v.w)) * r);
        asm volatile("st.shared.v2.b32 [%0], {%1,%2};" ::"r"(dst + b * YROW), "r"(lo), "r"(hi) : "memory");
    }
}

__global__ void __launch_bounds__(NTHREADS, 1)
fused_decode_kernel(const char* __restrict__ wqraw, unsigned* const cnt, const __grid_constant__ Maps maps, const char* __restrict__ Kc, const char* __restrict__ Vc,
                    const __nv_bfloat16* __restrict__ xA, const __nv_bfloat16* __restrict__ xB,
                    __nv_bfloat16* __restrict__ out, const uint32_t zero) {
    asm volatile("{\n.reg .pred p;\nsetp.eq.u32 p, %1, 0;\n@p cp.async.bulk.prefetch.L2.global [%0], %2;\n}"
                 ::"l"(wqraw + (size_t)blockIdx.x * (2 * CH)), "r"(threadIdx.x), "n"(CH) : "memory");
    unsigned epoch = 0;
    asm volatile("{\n.reg .pred p;\nsetp.eq.u32 p, %2, 64;\n@p atom.relaxed.gpu.global.add.u32 %0, [%1], 1;\n}"
                 : "+r"(epoch) : "l"(cnt), "r"(threadIdx.x) : "memory");
    extern __shared__ char smem_raw[];
    const uint32_t sm = ((uint32_t)__cvta_generic_to_shared(smem_raw) + 1023u) & ~1023u;
    const uint32_t bars = sm + OFF_BAR;
    const int cta = blockIdx.x, h = cta >> 2, j = cta & 3;
    uint64_t pol = 0;
    if (threadIdx.x == 0) {
        TS(0);
        asm volatile("createpolicy.fractional.L2::evict_first.b64 %0, 1.0;" : "=l"(pol));
#pragma unroll
        for (int i = 0; i < WIN; i++) mbar_init(bars + (B_WQB + i) * 8, 1);
        asm volatile("fence.mbarrier_init.release.cluster;" ::: "memory");
#pragma unroll
        for (int i = 0; i < WIN; i++) {
            mbar_expect(bars + (B_WQB + i) * 8, CH);
            tma3d(sm + OFF_S0 + i * CH, &maps.wqB + (i >> 1), j * 128 + (i & 1) * 64, h * 2, bars + (B_WQB + i) * 8, pol);
        }
    }
    const int tid = threadIdx.x < 64 ? threadIdx.x + 384 : threadIdx.x - 64, warp = tid >> 5, lane = tid & 31;

    if (warp == 12) {
        const size_t kvoff = ((size_t)(((j >> 1) * 32 + h) * 4096 + (j & 1) * 2048)) * 256;
        const char* kp = Kc + kvoff;
        const char* vp = Vc + kvoff;
        __syncwarp();
        bar_arrive(0, NTHREADS);
        bar_sync(3, 64);
        if (lane == 0) {
            uint32_t pb[WHI];
#pragma unroll
            for (int i = 0; i < WHI; i++) pb[i] = i < WHI - WIN ? (bars + B_WO * 8) | 1u : bars + (B_WQB + i - (WHI - WIN)) * 8;
            auto pace = [&](uint32_t bar, uint32_t par) {
                uint32_t it = 0;
                while (true) {
                    const uint32_t win = ldsv(sm + OFF_WIN);
                    uint32_t busy = 0;
#pragma unroll
                    for (int i = 0; i < WHI; i++) busy += mbar_test(pb[i] & ~1u, pb[i] & 1u) ^ 1u;
                    if (busy < win) break;
                    if (++it > SPIN_MAX) __trap();
                }
#pragma unroll
                for (int i = 0; i + 1 < WHI; i++) pb[i] = pb[i + 1];
                pb[WHI - 1] = bar | par;
            };
            auto side = [&](const CUtensorMap* m, uint32_t dst, int bidx, int c1, int c2) {
                const uint32_t bar = bars + bidx * 8;
                pace(bar, 0);
                mbar_expect(bar, CH);
                tma3d(dst, m, c1, c2, bar, pol);
            };
#pragma unroll 1
            for (int i = WIN; i < 6; i++)
                side(&maps.wqB + (i >> 1), sm + OFF_S0 + i * CH, B_WQB + i, j * 128 + (i & 1) * 64, h * 2);
            TS(1);
            uint32_t slot = 0, use = 0;
            int nuv = 0;
#pragma unroll 1
            for (int n = 0; n < 2 * NTILE; n++) {
                if (n == RING) {
                    mbar_wait(bars + B_FREE * 8, 0);
#pragma unroll 1
                    for (int q = 0; q < 4; q++) side(&maps.ckv, sm + OFF_S0 + q * CH, B_CKV + q, cta * 64 + q * 16, 0);
                }
                if (nuv < 2 && n > RING && (n >= 2 * NTILE - 8 || mbar_test(bars + B_FREE * 8, 1))) {
                    mbar_wait(bars + B_FREE * 8, 1);
                    side(&maps.wuv, sm + OFF_S1 + nuv * CH, B_WUV + nuv, j * 128 + nuv * 64, h * 2);
                    nuv++;
                }
                const uint32_t fb = bars + slot * 8;
                pace(fb, use & 1);
                mbar_wait(fb + B_EMPTY * 8, (use & 1) ^ 1);
                mbar_expect(fb, CH);
                bulk1d(sm + OFF_RING + slot * CH, ((n & 1) ? vp : kp) + (size_t)(n >> 1) * CH, fb, pol);
                if (n >= FINE_V || (n & 1)) {
                    asm volatile("red.relaxed.gpu.global.add.u32 [%0], %1;" ::"l"(cnt + 3), "r"(n >= FINE_V ? 1 : 2) : "memory");
                    stsv(sm + OFF_NOW, n + 1);
                }
                if (++slot == RING) { slot = 0; use++; }
            }
            TS(2);
            mbar_wait(bars + B_FREE * 8, 0);
            uint32_t it = 0;
#pragma unroll 1
            for (int q = 0; q < 8; q++) {
                const uint32_t bar = bars + (B_WO + q) * 8;
                mbar_expect(bar, CH / 2);
                while (true) {
                    const uint32_t t0 = ldsv(sm + OFF_TBOX);
                    if (t0 && gtime() - t0 + 16384u >= 16384u + q * BOX_NS) break;
                    if (++it > SPIN_MAX) __trap();
                }
                tma3d(sm + OFF_S0 + q * (CH / 2), &maps.woA + (cta & 1), (cta >> 4) * 512 + q * 64, (cta >> 1) & 7, bar, pol);
            }
            TS(3);
        }
    } else if (warp == 13) {
        if (lane == 0) {
#pragma unroll
            for (int i = 0; i < NBAR; i++)
                if (i < B_WQB || i >= B_WQB + WIN)
                    mbar_init(bars + i * 8, i == B_FREE ? 8 : (i >= B_EMPTY && i < B_EMPTY + RING) ? 4 : 1);
            asm volatile("fence.mbarrier_init.release.cluster;" ::: "memory");
#pragma unroll
            for (int i = 2; i < 8; i++) asm volatile("prefetch.tensormap [%0];" ::"l"(&maps.wqB + i) : "memory");
            stsv(sm + OFF_NOW, 0); stsv(sm + OFF_WIN, WIN); stsv(sm + OFF_TBOX, 0);
        }
        __syncwarp();
        bar_arrive(3, 64);
        bar_sync(0, NTHREADS);
        if (lane == 0) {
            const uint32_t base = (lds32(sm + OFF_TAG) - 1u) * (NCTA * 2 * NTILE);
            mbar_wait(bars + (B_WUK + 1) * 8, 0);
            uint32_t it = 0, tbox = 0;
            while (true) {
                const uint32_t n = ldsv(sm + OFF_NOW);
                uint32_t v;
                asm volatile("ld.relaxed.gpu.global.u32 %0, [%1];" : "=r"(v) : "l"(cnt + 3) : "memory");
                v -= base;
                if (v >= NCTA * EST_FROM && (v <= NCTA * EST_TO || !tbox)) {
                    const uint32_t est = (gtime() + (NCTA * 2 * NTILE - v) * BOX_NS / 64 + (uint32_t)(BOX_SHIFT + (cta * 37 & 127) * BOX_SPREAD / 128)) | 1u;
                    if (!tbox || (int)(est - tbox) < 0) { tbox = est; stsv(sm + OFF_TBOX, est); }
                }
                if (v >= NCTA * 2 * NTILE - GATE_W) break;
                const int diff = (int)(n * NCTA) - (int)v;
                stsv(sm + OFF_WIN, diff < -THETA ? WHI : WIN - (diff > THETA) - (v >= NCTA * END_V));
                if (++it > SPIN_MAX) __trap();
                __nanosleep(v < NCTA * FINE_V ? BACKOFF3 : BACKOFF2);
            }
            stsv(sm + OFF_WIN, WHI);
            TS(24);
        }
    } else if (warp < 4) {
        const int g = lane >> 2, t = lane & 3, i = lane >> 3, rr = lane & 7;
        if (tid == 0) sts32(sm + OFF_TAG, (epoch >> 7) + 1u);
        bar_sync(0, NTHREADS);
        const uint32_t tag = lds32(sm + OFF_TAG);
        {
            mbar_wait(bars + 8, 0);
            float q0, q1;
            ll_gather4(&g_e1[0][h * 4][tid], tag, q0, q1);
            sts16(sm + OFF_QB + tid * 2, f2bf((j >> 1) ? q1 : q0));
        }
        bar_sync(1, 128);
        if (tid == 0) TS(4);
        uint32_t qf[8][2];
#pragma unroll
        for (int c = 0; c < 8; c++) {
            const uint32_t a = sm + OFF_QB + (((c + g) & 7) * 8 + 2 * t) * 2;
            qf[c][0] = lds32(a); qf[c][1] = lds32(a + 128);
        }
        float acc[8][4];
#pragma unroll
        for (int c = 0; c < 8; c++) { acc[c][0] = acc[c][1] = acc[c][2] = acc[c][3] = 0.f; }
        float m = -INFINITY, l = 0.f;
        const bool diag = (t == (g >> 1));
        const uint32_t krow = sm + OFF_RING + (warp * 16 + rr + 8 * (i & 1)) * 256 + (i >> 1) * 128;
        const uint32_t vrow = sm + OFF_RING + (warp * 16 + rr + 8 * (i >> 1)) * 256 + (i & 1) * 128;
        uint32_t slot = 0, ph = 0;
        uint32_t* const e5own = pin(&g_e5[cta][tid]);
        uint32_t a[8][4], b0, b1;
#pragma unroll 1
        for (int tile = 0;; tile++) {
            mbar_wait(bars + slot * 8, ph);
#pragma unroll
            for (int c = 0; c < 8; c++) ldsm4(a[c], krow + slot * CH + (((c + rr) & 7) << 4));
            __syncwarp();
            if (lane == 0) mbar_arrive(bars + (B_EMPTY + slot) * 8 + ((a[0][0] | a[1][0] | a[2][0] | a[3][0] | a[4][0] | a[5][0] | a[6][0] | a[7][0]) & zero));
            if (++slot == RING) { slot = 0; ph ^= 1; }
            float s0[4] = {0.f, 0.f, 0.f, 0.f}, s1[4] = {0.f, 0.f, 0.f, 0.f};
#pragma unroll
            for (int c = 0; c < 8; c += 2) { mma(s0, a[c], qf[c][0], qf[c][1]); mma(s1, a[c + 1], qf[c + 1][0], qf[c + 1][1]); }
            float slo = (g & 1) ? s0[1] + s1[1] : s0[0] + s1[0];
            float shi = (g & 1) ? s0[3] + s1[3] : s0[2] + s1[2];
            slo = diag ? bfround(bfround(slo) * SCALE) : -INFINITY;
            shi = diag ? bfround(bfround(shi) * SCALE) : -INFINITY;
            int key = __float_as_int(fmaxf(slo, shi));
            key ^= (key >> 31) & 0x7fffffff;
            key = __reduce_max_sync(0xffffffffu, key);
            key ^= (key >> 31) & 0x7fffffff;
            const float mn = fmaxf(m, __int_as_float(key));
            const float alpha = ex2((m - mn) * LOG2E);
            m = mn;
            const float plo = ex2((slo - mn) * LOG2E), phi = ex2((shi - mn) * LOG2E);
            l = l * alpha + (plo + phi);
            b0 = (g & 1) ? pack2(0.f, plo) : pack2(plo, 0.f);
            b1 = (g & 1) ? pack2(0.f, phi) : pack2(phi, 0.f);
#pragma unroll
            for (int c = 0; c < 8; c++) { acc[c][0] *= alpha; acc[c][1] *= alpha; acc[c][2] *= alpha; acc[c][3] *= alpha; }
            if (tile == NTILE - 1) break;
            mbar_wait(bars + slot * 8, ph);
#pragma unroll
            for (int c = 0; c < 8; c++) ldsm4t(a[c], vrow + slot * CH + (((c + rr) & 7) << 4));
            __syncwarp();
            if (lane == 0) mbar_arrive(bars + (B_EMPTY + slot) * 8 + ((a[0][0] | a[1][0] | a[2][0] | a[3][0] | a[4][0] | a[5][0] | a[6][0] | a[7][0]) & zero));
            if (++slot == RING) { slot = 0; ph ^= 1; }
#pragma unroll
            for (int c = 0; c < 8; c++) mma(acc[c], a[c], b0, b1);
        }
#pragma unroll
        for (int o = 16; o; o >>= 1) l += __shfl_xor_sync(0xffffffffu, l, o);
        if (lane == 0) stsf2(sm + OFF_ML + warp * 8, m, l);
        mbar_wait(bars + B_S2 * 8, 0);
        bar_sync(1, 128);
        {
            const uint4 ml0 = lds128(sm + OFF_ML), ml1 = lds128(sm + OFF_ML + 16);
            const float m0 = __uint_as_float(ml0.x), m1 = __uint_as_float(ml0.z), m2 = __uint_as_float(ml1.x), m3 = __uint_as_float(ml1.z);
            const float M = fmaxf(fmaxf(m0, m1), fmaxf(m2, m3));
            const float L = (ex2((m0 - M) * LOG2E) * __uint_as_float(ml0.y) + ex2((m1 - M) * LOG2E) * __uint_as_float(ml0.w))
                          + (ex2((m2 - M) * LOG2E) * __uint_as_float(ml1.y) + ex2((m3 - M) * LOG2E) * __uint_as_float(ml1.w));
            const float f = ex2((m - M) * LOG2E) * rcp(L);
            if (tid == 0) post(e5own + (NCTA - cta) * 128 + cta, M * LOG2E + lg2(L));
            mbar_wait(bars + slot * 8, ph);
#pragma unroll
            for (int c = 0; c < 8; c++) ldsm4t(a[c], vrow + slot * CH + (((c + rr) & 7) << 4));
#pragma unroll
            for (int c = 0; c < 8; c++) mma(acc[c], a[c], b0, b1);
            if (tid == 0) TS(5);
            float v[2][8];
#pragma unroll
            for (int c = 0; c < 8; c++) { v[0][c] = acc[c][0] + acc[(c + 7) & 7][1]; v[1][c] = acc[c][2] + acc[(c + 7) & 7][3]; }
#pragma unroll
            for (int c = 0; c < 4; c++) { v[0][c] += __shfl_xor_sync(0xffffffffu, v[0][c + 4], 2); v[1][c] += __shfl_xor_sync(0xffffffffu, v[1][c + 4], 2); }
            const int src = (lane & ~3) | ((lane + 3) & 3);
#pragma unroll
            for (int c = 0; c < 2; c++) { v[0][c] += __shfl_sync(0xffffffffu, v[0][c + 2], src); v[1][c] += __shfl_sync(0xffffffffu, v[1][c + 2], src); }
            const uint32_t wa = sm + OFF_S2 + (warp * 160 + 16 * t + 8 * (t >> 1) + g) * 4;
            sts32(wa, __float_as_uint(v[0][0] * f)); sts32(wa + 32, __float_as_uint(v[0][1] * f));
            sts32(wa + 320, __float_as_uint(v[1][0] * f)); sts32(wa + 352, __float_as_uint(v[1][1] * f));
            bar_sync(1, 128);
            const uint32_t ra = sm + OFF_S2 + (tid + warp * 8) * 4;
            post(e5own, (ldsf(ra) + ldsf(ra + 640)) + (ldsf(ra + 1280) + ldsf(ra + 1920)));
        }
        if (tid == 0) TS(6);
        if (cta & 1) {
            const int c0 = (cta & ~15) + warp * 4;
            const uint32_t* p = e5own + ((c0 - cta) * 128 + lane * 4 - tid);
            const uint32_t* pl = e5own + ((NCTA - cta) * 128 + c0 - tid);
            uint4 x[5];
            bool need[5] = {true, true, true, true, true};
            uint32_t it = 0;
            while (true) {
#pragma unroll
                for (int q = 0; q < 5; q++) ld4_if(q < 4 ? p + q * 128 : pl, x[q], need[q]);
#pragma unroll
                for (int q = 0; q < 5; q++) need[q] = !x[q].x || !x[q].y || !x[q].z || !x[q].w;
                if (!__any_sync(0xffffffffu, need[0] | need[1] | need[2] | need[3] | need[4])) break;
                if (++it > SPIN_MAX) __trap();
            }
            merge_store(x, sm + OFF_Y + warp * YHEAD + lane * 8);
            bar_arrive(4, 256 + 128);
        }
        if (tid == 0) TS(16);
    } else {
        const int st = tid - 128, w = warp - 4;
        const int g = lane >> 2, t = lane & 3, i = lane >> 3, rr = lane & 7;
        if (t == 0) {
#pragma unroll
            for (int k = 0; k < 4; k++) ll_store2(&g_e1[k >> 1][cta][w * 16 + g + (k & 1) * 8], 0.f, 0.f, 0u);
        }
        if (st < 64) {
            const int which = st >> 5, b = (st >> 4) & 1, c = st & 15;
            const uint4 v = __ldg((const uint4*)((which ? xA : xB) + b * 512 + j * 128) + c);
            sts128(sm + OFF_XB + (which * 2 + b) * VROW + c * 16, v);
        }
        bar_sync(0, NTHREADS);
        const uint32_t tag = lds32(sm + OFF_TAG);
        float c[4];
#pragma unroll 1
        for (int which = 0; which < 2; which++) {
            matvecT(c, sm + OFF_S0 + which * 2 * CH, sm + OFF_XB + which * 2 * VROW, 2, bars + (B_WQB + which * 2) * 8, w, lane);
            if (t == 0) {
                ll_store2(&g_e1[which][cta][w * 16 + g], c[0], c[1], tag);
                ll_store2(&g_e1[which][cta][w * 16 + g + 8], c[2], c[3], tag);
            }
        }
        __syncwarp();
        if (lane == 0) mbar_arrive(bars + B_FREE * 8);
        if (st == 0) TS(8);
        if (st < 128) {
            float q0, q1;
            sleep_ns(POLL_DELAY);
            ll_gather4(&g_e1[1][h * 4][st], tag, q0, q1);
            sts16(sm + OFF_QA + st * 2, f2bf(q0)); sts16(sm + OFF_QA + VROW + st * 2, f2bf(q1));
        }
        bar_sync(2, 256);
        if (st == 0) TS(9);
        {
            const int row = w * 16 + rr + 8 * (i & 1);
            const uint32_t a0 = sm + OFF_S2 + (row >> 6) * CH + (row & 63) * 128;
            const uint32_t va = sm + OFF_QA + g * VROW + t * 4;
            float d[4] = {0.f, 0.f, 0.f, 0.f};
            c[0] = c[1] = c[2] = c[3] = 0.f;
            mbar_wait(bars + (B_WUK + (w >> 2)) * 8, 0);
#pragma unroll
            for (int ks = 0; ks < 8; ks++) {
                const int chunk = 2 * ks + (i >> 1);
                uint32_t a[4];
                ldsm4(a, a0 + (chunk >> 3) * 8192 + (((chunk & 7) ^ rr) << 4));
                const uint32_t b0 = (g < 2) ? lds32(va + ks * 32) : 0u, b1 = (g < 2) ? lds32(va + ks * 32 + 16) : 0u;
                if (ks & 1) mma(d, a, b0, b1); else mma(c, a, b0, b1);
            }
            if (t == 0) {
                const uint32_t qs = sm + OFF_QS + (w * 16 + g) * 2;
                sts16(qs, f2bf(c[0] + d[0])); sts16(qs + VROW, f2bf(c[1] + d[1]));
                sts16(qs + 16, f2bf(c[2] + d[2])); sts16(qs + VROW + 16, f2bf(c[3] + d[3]));
            }
            bar_sync(2, 256);
            if (w == 0) {
                const int b = lane >> 4, cc = lane & 15;
                g_qabs[(b * 32 + h) * 64 + ((j * 16 + cc) ^ (h & 7))] = lds128(sm + OFF_QS + b * VROW + cc * 16);
                __syncwarp();
                if (lane == 0) {
                    cnt_rendezvous(cnt + 1, tag * 128u, 18);
                    TS(10);
                    mbar_expect(bars + B_GATH * 8, 2 * CH);
                    bulk1d_n(sm + OFF_S2, g_qabs + (cta >> 6) * 2048, 2 * CH, bars + B_GATH * 8);
                }
                __syncwarp();
            }
        }
        mbar_wait(bars + B_GATH * 8, 0);
        if (st == 0) TS(11);
        {
            const int mt = w & 1, kg = w >> 1;
            const uint32_t qa = sm + OFF_S2 + (mt * 16 + rr + 8 * (i & 1)) * 1024;
            const uint32_t ka = sm + OFF_S0 + kg * CH + (rr + 8 * (i >> 1)) * 128;
            float s0[4] = {0.f, 0.f, 0.f, 0.f}, s1[4] = {0.f, 0.f, 0.f, 0.f};
            mbar_wait(bars + (B_CKV + kg) * 8, 0);
#pragma unroll 2
            for (int gq = 0; gq < 8; gq++) {
#pragma unroll
                for (int k4 = 0; k4 < 4; k4++) {
                    uint32_t a[4], b[4];
                    ldsm4(a, qa + gq * 128 + (((2 * k4 + (i >> 1)) ^ rr) << 4));
                    ldsm4(b, ka + gq * 2048 + (((2 * k4 + (i & 1)) ^ rr) << 4));
                    mma(s0, a, b[0], b[1]);
                    mma(s1, a, b[2], b[3]);
                }
            }
            const uint32_t sa = sm + OFF_SC + ((mt * 16 + g) * 68 + kg * 16 + 2 * t) * 4;
            stsf2(sa, s0[0], s0[1]); stsf2(sa + 32, s1[0], s1[1]);
            stsf2(sa + 8 * 68 * 4, s0[2], s0[3]); stsf2(sa + 8 * 68 * 4 + 32, s1[2], s1[3]);
        }
        bar_sync(2, 256);
        {
            const int head = w * 4 + i;
            const uint32_t sa = sm + OFF_SC + (head * 68 + rr * 8) * 4;
            const uint4 u0 = lds128(sa), u1 = lds128(sa + 16);
            float s[8] = {__uint_as_float(u0.x), __uint_as_float(u0.y), __uint_as_float(u0.z), __uint_as_float(u0.w),
                          __uint_as_float(u1.x), __uint_as_float(u1.y), __uint_as_float(u1.z), __uint_as_float(u1.w)};
            float mx = s[0];
#pragma unroll
            for (int k = 1; k < 8; k++) mx = fmaxf(mx, s[k]);
#pragma unroll
            for (int o = 1; o < 8; o <<= 1) mx = fmaxf(mx, __shfl_xor_sync(0xffffffffu, mx, o));
            float sum = 0.f;
#pragma unroll
            for (int k = 0; k < 8; k++) { s[k] = ex2((s[k] - mx) * (SCALE * LOG2E)); sum += s[k]; }
#pragma unroll
            for (int o = 1; o < 8; o <<= 1) sum += __shfl_xor_sync(0xffffffffu, sum, o);
            const float inv = __fdividef(1.f, sum);
            uint4 p;
            p.x = pack2(s[0] * inv, s[1] * inv); p.y = pack2(s[2] * inv, s[3] * inv);
            p.z = pack2(s[4] * inv, s[5] * inv); p.w = pack2(s[6] * inv, s[7] * inv);
            sts128(sm + OFF_P + head * 128 + ((rr ^ (head & 7)) << 4), p);
            if (rr == 0) ((float*)g_lse)[head * 128 + cta] = mx * (SCALE * LOG2E) + lg2(sum);
        }
        bar_sync(2, 256);
        {
            float o[2][8][4];
#pragma unroll
            for (int mt = 0; mt < 2; mt++)
#pragma unroll
                for (int n = 0; n < 8; n++) { o[mt][n][0] = o[mt][n][1] = o[mt][n][2] = o[mt][n][3] = 0.f; }
            const uint32_t pa = sm + OFF_P + (rr + 8 * (i & 1)) * 128;
            const uint32_t va = sm + OFF_S0 + w * 2048 + (rr + 8 * (i & 1)) * 128;
#pragma unroll 1
            for (int kq = 0; kq < 4; kq++) {
                uint32_t a0[4], a1[4];
                ldsm4(a0, pa + (((2 * kq + (i >> 1)) ^ rr) << 4));
                ldsm4(a1, pa + 2048 + (((2 * kq + (i >> 1)) ^ rr) << 4));
#pragma unroll
                for (int n = 0; n < 8; n += 2) {
                    uint32_t b[4];
                    ldsm4t(b, va + kq * CH + (((n + (i >> 1)) ^ rr) << 4));
                    mma(o[0][n], a0, b[0], b[1]); mma(o[1][n], a1, b[0], b[1]);
                    mma(o[0][n + 1], a0, b[2], b[3]); mma(o[1][n + 1], a1, b[2], b[3]);
                }
            }
#pragma unroll
            for (int mt = 0; mt < 2; mt++)
#pragma unroll
                for (int hf = 0; hf < 2; hf++) {
                    const uint32_t dst = sm + OFF_S2 + (mt * 16 + hf * 8 + g) * 1024 + w * 128 + t * 16;
#pragma unroll
                    for (int nb = 0; nb < 2; nb++) {
                        uint4 v;
                        v.x = pack2(o[mt][nb * 4 + 0][hf * 2], o[mt][nb * 4 + 0][hf * 2 + 1]);
                        v.y = pack2(o[mt][nb * 4 + 1][hf * 2], o[mt][nb * 4 + 1][hf * 2 + 1]);
                        v.z = pack2(o[mt][nb * 4 + 2][hf * 2], o[mt][nb * 4 + 2][hf * 2 + 1]);
                        v.w = pack2(o[mt][nb * 4 + 3][hf * 2], o[mt][nb * 4 + 3][hf * 2 + 1]);
                        sts128(dst + nb * 64, v);
                    }
                }
            asm volatile("fence.proxy.async.shared::cta;" ::: "memory");
            __syncwarp();
            if (lane == 0) mbar_arrive(bars + B_FREE * 8);
            g_e4[cta][st] = 0u;
            if (st < 128) g_e5[cta][st] = 0u;
            else if (cta == 0) g_e5[NCTA][st - 128] = 0u;
            if (st >= 248) ((uint32_t*)out)[cta * 8 + st - 248] = 0u;
        }
        bar_sync(2, 256);
        if (st == 0) {
            TS(12);
#pragma unroll 1
            for (int k = 0; k < ST_SPLIT; k++) {
                asm volatile("cp.async.bulk.tensor.3d.global.shared::cta.bulk_group [%0, {%2,%3,%4}], [%1];"
                             ::"l"(&maps.ctxp), "r"(sm + OFF_S2 + k * (2 * CH / ST_SPLIT)), "r"(0), "r"(cta), "r"(k * (128 / ST_SPLIT)) : "memory");
                if (k + 1 < ST_SPLIT) __nanosleep(ST_GAP);
            }
            asm volatile("cp.async.bulk.commit_group;" ::: "memory");
            asm volatile("cp.async.bulk.wait_group 0;" ::: "memory");
            cnt_rendezvous(cnt + 2, tag * 128u, 20);
            TS(13);
            mbar_expect(bars + B_GATH * 8, 2 * CH + 512);
            bulk1d_n(sm + OFF_LSE, g_lse + h * 32, 512, bars + B_GATH * 8);
#pragma unroll 1
            for (int k = 0; k < ST_SPLIT; k++) {
                bulk1d_n(sm + OFF_S2 + k * (2 * CH / ST_SPLIT), g_ctxp + cta * 2048 + k * (2048 / ST_SPLIT), 2 * CH / ST_SPLIT, bars + B_GATH * 8);
                __nanosleep(LD_GAP);
            }
        }
        __syncwarp();
        {
            mbar_wait(bars + B_GATH * 8, 1);
            if (st == 0) TS(22);
            uint4 v[8];
#pragma unroll
            for (int k = 0; k < 8; k++) v[k] = lds128(sm + OFF_S2 + (k * 256 + st) * 16);
            float ls[4];
#pragma unroll
            for (int k = 0; k < 4; k++) ls[k] = ldsf(sm + OFF_LSE + (k * 32 + lane) * 4);
            float m0 = fmaxf(ls[0], ls[1]), m1 = fmaxf(ls[2], ls[3]);
#pragma unroll
            for (int o = 16; o; o >>= 1) { m0 = fmaxf(m0, __shfl_xor_sync(0xffffffffu, m0, o)); m1 = fmaxf(m1, __shfl_xor_sync(0xffffffffu, m1, o)); }
            ls[0] = ex2(ls[0] - m0); ls[1] = ex2(ls[1] - m0); ls[2] = ex2(ls[2] - m1); ls[3] = ex2(ls[3] - m1);
            float z0 = ls[0] + ls[1], z1 = ls[2] + ls[3];
#pragma unroll
            for (int o = 16; o; o >>= 1) { z0 += __shfl_xor_sync(0xffffffffu, z0, o); z1 += __shfl_xor_sync(0xffffffffu, z1, o); }
            z0 = __fdividef(1.f, z0); z1 = __fdividef(1.f, z1);
            ls[0] *= z0; ls[1] *= z0; ls[2] *= z1; ls[3] *= z1;
            float a[2][8];
#pragma unroll
            for (int e = 0; e < 8; e++) a[0][e] = a[1][e] = 0.f;
            const int rg = st >> 4;
#pragma unroll
            for (int k = 0; k < 8; k++) {
                const float wt = __shfl_sync(0xffffffffu, ls[k >> 1], rg + 16 * (k & 1));
                const uint32_t u[4] = {v[k].x, v[k].y, v[k].z, v[k].w};
#pragma unroll
                for (int e = 0; e < 4; e++) {
                    a[k >> 2][2 * e] += wt * __uint_as_float(u[e] << 16);
                    a[k >> 2][2 * e + 1] += wt * __uint_as_float(u[e] & 0xffff0000u);
                }
            }
            const int b = lane >> 4, u16 = lane & 15;
            const uint32_t ra = sm + OFF_SC + (w * 256 + b * 128 + (u16 >> 3) * 64 + ((u16 >> 2) & 1) * 32 + (u16 & 3) * 2) * 4;
#pragma unroll
            for (int e = 0; e < 8; e += 2) {
                const float k0 = b ? a[1][e] : a[0][e], k1 = b ? a[1][e + 1] : a[0][e + 1];
                const float s0 = b ? a[0][e] : a[1][e], s1 = b ? a[0][e + 1] : a[1][e + 1];
                stsf2(ra + (e >> 1) * 32, k0 + __shfl_xor_sync(0xffffffffu, s0, 16), k1 + __shfl_xor_sync(0xffffffffu, s1, 16));
            }
            bar_sync(2, 256);
            if (st == 0) mbar_arrive(bars + B_S2 * 8);
            float s = 0.f;
#pragma unroll
            for (int k = 0; k < 8; k++) s += ldsf(sm + OFF_SC + (k * 256 + st) * 4);
            const float hi = bfround(s);
            const uint32_t ca = sm + OFF_CC + (st >> 7) * VROW + (st & 127) * 2;
            sts16(ca, f2bf(hi)); sts16(ca + 2 * VROW, f2bf(s - hi));
            bar_sync(2, 256);
        }
        matvecT(c, sm + OFF_S1, sm + OFF_CC, 4, bars + B_WUV * 8, w, lane);
#pragma unroll
        for (int k = 0; k < 4; k++) c[k] += __shfl_xor_sync(0xffffffffu, c[k], 1);
        post(&g_e4[cta][(t & 1) * 128 + w * 16 + (t >> 1) * 8 + g], t == 0 ? c[0] : t == 1 ? c[1] : t == 2 ? c[2] : c[3]);
        __syncwarp();
        if (lane == 0) mbar_arrive(bars + B_FREE * 8);
        if (st == 0) TS(23);
        if (st < 128) sts32(sm + OFF_PAIR + st * 4, EMPTY);
        if (!(cta & 1)) {
            const uint32_t* p = &g_e4[(cta & ~15) + (w >> 1) * 4][(w & 1) * 128 + lane * 4];
            uint4 x[4];
            bool need[4] = {true, true, true, true};
            uint32_t it = 0;
            sleep_ns(POLL_DELAY2);
            while (true) {
#pragma unroll
                for (int q = 0; q < 4; q++) ld4_if(p + q * 256, x[q], need[q]);
#pragma unroll
                for (int q = 0; q < 4; q++) need[q] = !x[q].x || !x[q].y || !x[q].z || !x[q].w;
                if (!__any_sync(0xffffffffu, need[0] | need[1] | need[2] | need[3])) break;
                if (++it > SPIN_MAX) __trap();
                __nanosleep(BACKOFF);
            }
            auto sum4 = [](uint32_t a, uint32_t b, uint32_t c, uint32_t d) {
                return (__uint_as_float(~a) + __uint_as_float(~b)) + (__uint_as_float(~c) + __uint_as_float(~d));
            };
            asm volatile("st.shared.v2.b32 [%0], {%1,%2};" ::"r"(sm + OFF_Y + (w & 1) * YROW + (w >> 1) * YHEAD + lane * 8),
                         "r"(pack2(sum4(x[0].x, x[1].x, x[2].x, x[3].x), sum4(x[0].y, x[1].y, x[2].y, x[3].y))),
                         "r"(pack2(sum4(x[0].z, x[1].z, x[2].z, x[3].z), sum4(x[0].w, x[1].w, x[2].w, x[3].w))) : "memory");
        }
        if (st == 0) TS(14);
        bar_sync(2, 256);
        {
            const int hf = w >> 2, cg = w & 3;
            const uint32_t a0 = sm + OFF_S0 + hf * 8192 + (rr + 8 * (i >> 1)) * 128 + (((2 * cg + (i & 1)) ^ rr) << 4);
            const uint32_t va = sm + OFF_Y + (lane >> 1 & 1) * YROW + (lane & 1) * YHEAD + hf * 128 + i * 16;
            const uint32_t wb = bars + (B_WO + hf) * 8;
            const uint32_t pa = sm + OFF_PAIR + (cg * 32 + lane) * 4;
            const int col = (t & 1) * 1024 + (cta & 1) * 512 + (cta >> 1 & 7) * 64 + cg * 16 + (t >> 1) * 8 + g;
            __nv_bfloat16* const outp = pin(out + (col & ~1));
            const bool up = t >= 2, odd = g & 1;
            uint32_t a[4][4][4], b[4][4];
            float d[2][4][4];
#pragma unroll
            for (int k = 0; k < 8; k++) d[k >> 2][k & 3][0] = d[k >> 2][k & 3][1] = d[k >> 2][k & 3][2] = d[k >> 2][k & 3][3] = 0.f;
            auto load_w = [&](int hd) {
                mbar_wait(wb + hd * 16, 0);
#pragma unroll
                for (int k = 0; k < 4; k++) ldsm4t(a[hd][k], a0 + hd * CH + k * 2048);
            };
            auto load_y = [&]() {
#pragma unroll
                for (int q = 0; q < 4; q++) ldsm4(b[q], va + (q >> 1) * 2 * YHEAD + (q & 1) * 64);
            };
            auto head = [&](int hd) {
#pragma unroll
                for (int k = 0; k < 4; k++) mma(d[hd & 1][k], a[hd][k], b[(hd & 2) + (k >> 1)][(k & 1) * 2], b[(hd & 2) + (k >> 1)][(k & 1) * 2 + 1]);
            };
            if (cta & 1) {
                load_w(0); load_w(1);
                bar_sync(4, 256 + 128);
                load_y();
                head(0); head(1);
            } else {
                load_y();
                load_w(0); head(0);
                load_w(1); head(1);
            }
            if (st == 0) TS(25);
            load_w(2); head(2);
            float z = up ? (d[0][0][2] + d[0][1][2]) + (d[0][2][2] + d[0][3][2]) : (d[0][0][0] + d[0][1][0]) + (d[0][2][0] + d[0][3][0]);
            mbar_wait_uni(wb + 48);
            if (st == 0) TS(26);
            uint32_t other = ldsv(pa);
#pragma unroll
            for (int k = 0; k < 4; k++) ldsm4t(a[3][k], a0 + 3 * CH + k * 2048);
            head(3);
            z += other != EMPTY ? __uint_as_float(other) : 0.f;
            float z1 = z, z3 = z;
#pragma unroll
            for (int k = 0; k < 3; k++) { z1 += d[1][k][1]; z3 += d[1][k][3]; }
            z = up ? z3 + d[1][3][3] : z1 + d[1][3][1];
            if (st == 0) TS(17);
            asm volatile("{\n.reg .pred p;\nsetp.eq.u32 p, %2, %3;\n@p bra FIRST;\nred.relaxed.gpu.global.add.noftz.bf16x2 [%0], %1;\nexit;\nFIRST:\n}"
                         ::"l"(outp), "r"(odd ? pack2(0.f, z) : pack2(z, 0.f)), "r"(other), "n"(EMPTY) : "memory");
            asm volatile("atom.shared.exch.b32 %0, [%1], %2;" : "=r"(other) : "r"(pa), "r"(__float_as_uint(z)) : "memory");
            z += __uint_as_float(other);
            asm volatile("{\n.reg .pred p;\nsetp.eq.u32 p, %2, %3;\n@p exit;\nred.relaxed.gpu.global.add.noftz.bf16x2 [%0], %1;\n}"
                         ::"l"(outp), "r"(odd ? pack2(0.f, z) : pack2(z, 0.f)), "r"(other), "n"(EMPTY) : "memory");
        }
    }
}

typedef CUresult (*EncodeFn)(CUtensorMap*, CUtensorMapDataType, cuuint32_t, void*, const cuuint64_t*, const cuuint64_t*,
                             const cuuint32_t*, const cuuint32_t*, CUtensorMapInterleave, CUtensorMapSwizzle,
                             CUtensorMapL2promotion, CUtensorMapFloatOOBfill);

void make_map(EncodeFn enc, CUtensorMap* m, void* p, unsigned rows, unsigned cols, unsigned br, unsigned bg) {
    cuuint64_t gd[3] = {64, rows, cols / 64};
    cuuint64_t gs[2] = {(cuuint64_t)cols * 2, 128};
    cuuint32_t bx[3] = {64, br, bg};
    cuuint32_t es[3] = {1, 1, 1};
    enc(m, CU_TENSOR_MAP_DATA_TYPE_BFLOAT16, 3, p, gd, gs, bx, es, CU_TENSOR_MAP_INTERLEAVE_NONE,
        CU_TENSOR_MAP_SWIZZLE_128B, CU_TENSOR_MAP_L2_PROMOTION_L2_128B, CU_TENSOR_MAP_FLOAT_OOB_FILL_NONE);
}

}

extern "C" void kernel_launch(void* const* d_in, const int* in_sizes, int n_in, void* d_out, int out_size) {
    static EncodeFn enc = nullptr;
    if (!enc) {
        void* fn = nullptr;
        cudaDriverEntryPointQueryResult qr;
        cudaGetDriverEntryPoint("cuTensorMapEncodeTiled", &fn, cudaEnableDefault, &qr);
        enc = (EncodeFn)fn;
        cudaFuncSetAttribute(fused_decode_kernel, cudaFuncAttributeMaxDynamicSharedMemorySize, SMEM_BYTES);
    }
    Maps maps;
    make_map(enc, &maps.wqB, d_in[9], 512, 4096, 64, 2);
    make_map(enc, &maps.wqA, d_in[2], 512, 4096, 64, 2);
    make_map(enc, &maps.wuk, d_in[3], 512, 4096, 64, 2);
    make_map(enc, &maps.wuv, d_in[4], 512, 4096, 64, 2);
    make_map(enc, &maps.woA, d_in[5], 4096, 512, 64, 1);
    make_map(enc, &maps.woB, d_in[10], 4096, 512, 64, 1);
    make_map(enc, &maps.ckv, d_in[1], 8192, 512, 16, 8);
    {
        void* p = nullptr;
        cudaGetSymbolAddress(&p, g_ctxp);
        cuuint64_t gd[3] = {128, 128, 128};
        cuuint64_t gs[2] = {256, 32768};
        cuuint32_t bx[3] = {128, 1, 128 / ST_SPLIT};
        cuuint32_t es[3] = {1, 1, 1};
        enc(&maps.ctxp, CU_TENSOR_MAP_DATA_TYPE_BFLOAT16, 3, p, gd, gs, bx, es, CU_TENSOR_MAP_INTERLEAVE_NONE,
            CU_TENSOR_MAP_SWIZZLE_NONE, CU_TENSOR_MAP_L2_PROMOTION_NONE, CU_TENSOR_MAP_FLOAT_OOB_FILL_NONE);
    }
    void* cnt = nullptr;
    cudaGetSymbolAddress(&cnt, g_cnt);
    fused_decode_kernel<<<NCTA, NTHREADS, SMEM_BYTES>>>((const char*)d_in[9], (unsigned*)cnt, maps, (const char*)d_in[7], (const char*)d_in[8],
                                                         (const __nv_bfloat16*)d_in[0], (const __nv_bfloat16*)d_in[6],
                                                         (__nv_bfloat16*)d_out, 0u);
}
```

```cpp
#include <cuda_runtime.h>
#include <cuda.h>
#include <cuda_bf16.h>
#include <stdint.h>

#define RING 7
#define WIN 4
#define WHI 5
#define THETA 64
#define END_V 40
#define GATE_W 64
#define BOX_NS 319
#define BOX_SHIFT 5
#define BOX_SPREAD 150
#define EST_FROM 57
#define EST_TO 62
#define POLL_DELAY 3000
#define POLL_DELAY2 2500
#define ST_SPLIT 8
#define ST_GAP 500
#define LD_GAP 300
#define BACKOFF 200
#define BACKOFF_RV 800
#define FINE_V 52
#define BACKOFF2 100
#define BACKOFF3 300

namespace {

constexpr int NCTA = 128;
constexpr int NTHREADS = 448;
constexpr uint32_t CH = 16384;
constexpr int NTILE = 32;

constexpr uint32_t OFF_RING = 0;
constexpr uint32_t OFF_S0 = RING * CH;
constexpr uint32_t OFF_S1 = OFF_S0 + 2 * CH;
constexpr uint32_t OFF_S2 = OFF_S1 + 2 * CH;
constexpr uint32_t OFF_P = OFF_S2 + 2 * CH;
constexpr uint32_t OFF_SC = OFF_P + 4096;
constexpr uint32_t VROW = 272;
constexpr uint32_t OFF_XB = OFF_SC + 8704;
constexpr uint32_t OFF_XA = OFF_XB + 2 * VROW;
constexpr uint32_t OFF_QA = OFF_XA + 2 * VROW;
constexpr uint32_t OFF_QS = OFF_QA + 2 * VROW;
constexpr uint32_t OFF_CC = OFF_QS + 2 * VROW;
constexpr uint32_t OFF_QB = OFF_CC + 4 * VROW;
constexpr uint32_t YHEAD = 288, YROW = 4 * YHEAD + 16;
constexpr uint32_t OFF_Y = OFF_P;
constexpr uint32_t OFF_PAIR = OFF_P + 2 * YROW;
constexpr uint32_t EMPTY = 0xffffffffu;
constexpr uint32_t OFF_LSE = OFF_QB + 256;
constexpr uint32_t OFF_ML = OFF_LSE + 512;
constexpr uint32_t OFF_TAG = OFF_ML + 32;
constexpr uint32_t OFF_NOW = OFF_TAG + 4;
constexpr uint32_t OFF_WIN = OFF_TAG + 8;
constexpr uint32_t OFF_TBOX = OFF_TAG + 12;
constexpr uint32_t OFF_BAR = OFF_TAG + 16;
constexpr int B_EMPTY = RING;
constexpr int B_WQB = 2 * RING;
constexpr int B_WQA = B_WQB + 2;
constexpr int B_WUK = B_WQA + 2;
constexpr int B_WUV = B_WUK + 2;
constexpr int B_CKV = B_WUV + 2;
constexpr int B_WO = B_CKV + 4;
constexpr int B_FREE = B_WO + 8;
constexpr int B_GATH = B_FREE + 1;
constexpr int B_S2 = B_GATH + 1;
constexpr int NBAR = B_S2 + 1;
constexpr uint32_t TS_OFF = OFF_BAR + NBAR * 8;
constexpr uint32_t SMEM_USED = TS_OFF;
constexpr uint32_t SMEM_BYTES = SMEM_USED + 1024;
static_assert(SMEM_BYTES <= 232448, "smem");
static_assert(RING >= WHI && WHI >= WIN && WIN >= 3 && WIN <= 6 && FINE_V % 2 == 0, "windows");

constexpr float LOG2E = 1.4426950408889634f;
constexpr float SCALE = 0.08838834764831845f;
#define SPIN_LOG 22
constexpr uint32_t SPIN_MAX = 1u << SPIN_LOG;

struct Maps { CUtensorMap wqB, wqA, wuk, wuv, woA, woB, ckv, ctxp; };

struct Scratch {
    unsigned cnt[64];
    ulonglong2 e1[2][NCTA][128];
    uint4 qabs[2 * 32 * 64];
    float4 lse[32 * 32];
    uint32_t e4[NCTA][256];
    uint32_t e5[NCTA + 2][128];
    uint4 ctxp[NCTA * 128 * 16];
};
__device__ __align__(256) Scratch g_scratch;

#define TS(k) do {} while (0)

__device__ __forceinline__ void mbar_init(uint32_t b, int c) { asm volatile("mbarrier.init.shared::cta.b64 [%0], %1;" ::"r"(b), "r"(c) : "memory"); }
__device__ __forceinline__ void mbar_expect(uint32_t b, uint32_t bytes) { asm volatile("mbarrier.arrive.expect_tx.shared::cta.b64 _, [%0], %1;" ::"r"(b), "r"(bytes) : "memory"); }
__device__ __forceinline__ void mbar_arrive(uint32_t b) { asm volatile("mbarrier.arrive.shared::cta.b64 _, [%0];" ::"r"(b) : "memory"); }
__device__ __forceinline__ void mbar_wait(uint32_t b, uint32_t ph) {
    uint32_t ok, it = 0;
    do {
        asm volatile("{\n.reg .pred p;\nmbarrier.try_wait.parity.shared::cta.b64 p, [%1], %2;\nselp.u32 %0, 1, 0, p;\n}" : "=r"(ok) : "r"(b), "r"(ph) : "memory");
        if (++it > SPIN_MAX) __trap();
    } while (!ok);
}
__device__ __forceinline__ void mbar_wait_uni(uint32_t b) {
    asm volatile("{\n.reg .pred p, q;\n.reg .u32 n;\nmov.u32 n, 0;\nAGAIN:\nadd.u32 n, n, 1;\nsetp.gt.u32 q, n, %1;\n"
                 "mbarrier.try_wait.parity.shared::cta.b64 p, [%0], 0;\n@q trap;\n@!p bra.uni AGAIN;\n}" ::"r"(b), "n"(SPIN_MAX) : "memory");
}
__device__ __forceinline__ uint32_t mbar_test(uint32_t b, uint32_t ph) {
    uint32_t ok;
    asm volatile("{\n.reg .pred p;\nmbarrier.test_wait.parity.shared::cta.b64 p, [%1], %2;\nselp.u32 %0, 1, 0, p;\n}" : "=r"(ok) : "r"(b), "r"(ph) : "memory");
    return ok;
}
__device__ __forceinline__ void bulk1d(uint32_t dst, const void* src, uint32_t bar, uint64_t pol) {
    asm volatile("cp.async.bulk.shared::cluster.global.mbarrier::complete_tx::bytes.L2::cache_hint [%0], [%1], %2, [%3], %4;"
                 ::"r"(dst), "l"(src), "n"(CH), "r"(bar), "l"(pol) : "memory");
}
__device__ __forceinline__ void bulk1d_n(uint32_t dst, const void* src, uint32_t bytes, uint32_t bar) {
    asm volatile("cp.async.bulk.shared::cluster.global.mbarrier::complete_tx::bytes [%0], [%1], %2, [%3];"
                 ::"r"(dst), "l"(src), "r"(bytes), "r"(bar) : "memory");
}
__device__ __forceinline__ void tma3d(uint32_t dst, const CUtensorMap* map, int c1, int c2, uint32_t bar, uint64_t pol) {
    asm volatile("cp.async.bulk.tensor.3d.shared::cluster.global.mbarrier::complete_tx::bytes.L2::cache_hint [%0], [%1, {%3,%4,%5}], [%2], %6;"
                 ::"r"(dst), "l"(map), "r"(bar), "r"(0), "r"(c1), "r"(c2), "l"(pol) : "memory");
}
__device__ __forceinline__ void bar_sync(int id, int n) { asm volatile("barrier.cta.sync %0, %1;" ::"r"(id), "r"(n) : "memory"); }
__device__ __forceinline__ void bar_arrive(int id, int n) { asm volatile("barrier.cta.arrive %0, %1;" ::"r"(id), "r"(n) : "memory"); }
__device__ __forceinline__ void ldsm4(uint32_t (&r)[4], uint32_t a) {
    asm volatile("ldmatrix.sync.aligned.m8n8.x4.shared.b16 {%0,%1,%2,%3}, [%4];" : "=r"(r[0]), "=r"(r[1]), "=r"(r[2]), "=r"(r[3]) : "r"(a) : "memory");
}
__device__ __forceinline__ void ldsm4t(uint32_t (&r)[4], uint32_t a) {
    asm volatile("ldmatrix.sync.aligned.m8n8.x4.trans.shared.b16 {%0,%1,%2,%3}, [%4];" : "=r"(r[0]), "=r"(r[1]), "=r"(r[2]), "=r"(r[3]) : "r"(a) : "memory");
}
__device__ __forceinline__ void mma(float (&c)[4], const uint32_t (&a)[4], uint32_t b0, uint32_t b1) {
    asm volatile("mma.sync.aligned.m16n8k16.row.col.f32.bf16.bf16.f32 {%0,%1,%2,%3}, {%4,%5,%6,%7}, {%8,%9}, {%0,%1,%2,%3};"
                 : "+f"(c[0]), "+f"(c[1]), "+f"(c[2]), "+f"(c[3]) : "r"(a[0]), "r"(a[1]), "r"(a[2]), "r"(a[3]), "r"(b0), "r"(b1));
}
__device__ __forceinline__ uint32_t lds32(uint32_t a) { uint32_t v; asm volatile("ld.shared.b32 %0, [%1];" : "=r"(v) : "r"(a) : "memory"); return v; }
__device__ __forceinline__ uint32_t ldsv(uint32_t a) { uint32_t v; asm volatile("ld.volatile.shared.b32 %0, [%1];" : "=r"(v) : "r"(a) : "memory"); return v; }
__device__ __forceinline__ void stsv(uint32_t a, uint32_t v) { asm volatile("st.volatile.shared.b32 [%0], %1;" ::"r"(a), "r"(v) : "memory"); }
__device__ __forceinline__ float ldsf(uint32_t a) { float v; asm volatile("ld.shared.f32 %0, [%1];" : "=f"(v) : "r"(a) : "memory"); return v; }
__device__ __forceinline__ uint4 lds128(uint32_t a) { uint4 v; asm volatile("ld.shared.v4.b32 {%0,%1,%2,%3}, [%4];" : "=r"(v.x), "=r"(v.y), "=r"(v.z), "=r"(v.w) : "r"(a) : "memory"); return v; }
__device__ __forceinline__ void sts16(uint32_t a, uint16_t v) { asm volatile("st.shared.b16 [%0], %1;" ::"r"(a), "h"(v) : "memory"); }
__device__ __forceinline__ void sts32(uint32_t a, uint32_t v) { asm volatile("st.shared.b32 [%0], %1;" ::"r"(a), "r"(v) : "memory"); }
__device__ __forceinline__ void stsf2(uint32_t a, float x, float y) { asm volatile("st.shared.v2.f32 [%0], {%1,%2};" ::"r"(a), "f"(x), "f"(y) : "memory"); }
__device__ __forceinline__ void sts128(uint32_t a, uint4 v) { asm volatile("st.shared.v4.b32 [%0], {%1,%2,%3,%4};" ::"r"(a), "r"(v.x), "r"(v.y), "r"(v.z), "r"(v.w) : "memory"); }
__device__ __forceinline__ uint16_t f2bf(float x) { return __bfloat16_as_ushort(__float2bfloat16_rn(x)); }
__device__ __forceinline__ float bfround(float x) { return __bfloat162float(__float2bfloat16_rn(x)); }
__device__ __forceinline__ uint32_t pack2(float lo, float hi) { uint32_t r; asm("cvt.rn.bf16x2.f32 %0, %1, %2;" : "=r"(r) : "f"(hi), "f"(lo)); return r; }
__device__ __forceinline__ float ex2(float x) { float r; asm("ex2.approx.ftz.f32 %0, %1;" : "=f"(r) : "f"(x)); return r; }
__device__ __forceinline__ float lg2(float x) { float r; asm("lg2.approx.ftz.f32 %0, %1;" : "=f"(r) : "f"(x)); return r; }

__device__ __forceinline__ float rcp(float x) { float r; asm("rcp.approx.ftz.f32 %0, %1;" : "=f"(r) : "f"(x)); return r; }

__device__ __forceinline__ uint32_t gtime() { uint32_t t; asm volatile("mov.u32 %0, %globaltimer_lo;" : "=r"(t)::"memory"); return t; }
__device__ __forceinline__ void sleep_ns(uint32_t ns) {
    uint32_t t0, t;
    asm volatile("mov.u32 %0, %clock;" : "=r"(t0));
    do { __nanosleep(200); asm volatile("mov.u32 %0, %clock;" : "=r"(t)); } while (t - t0 < 2 * ns);
}

__device__ __forceinline__ void ll_store2(ulonglong2* p, float a, float b, uint32_t tag) {
    unsigned long long x = ((unsigned long long)tag << 32) | __float_as_uint(a);
    unsigned long long y = ((unsigned long long)tag << 32) | __float_as_uint(b);
    asm volatile("st.relaxed.gpu.global.v2.b64 [%0], {%1,%2};" ::"l"(p), "l"(x), "l"(y) : "memory");
}
__device__ __forceinline__ void ll_ld2(const void* p, unsigned long long& x, unsigned long long& y) {
    asm volatile("ld.relaxed.gpu.global.v2.b64 {%0,%1}, [%2];" : "=l"(x), "=l"(y) : "l"(p) : "memory");
}
__device__ __forceinline__ void ll_gather4(const ulonglong2* p, uint32_t tag, float& r0, float& r1) {
    unsigned long long x[4], y[4]; uint32_t it = 0;
    while (true) {
        bool ok = true;
#pragma unroll
        for (int k = 0; k < 4; k++) ll_ld2(p + k * 128, x[k], y[k]);
#pragma unroll
        for (int k = 0; k < 4; k++) ok = ok && (uint32_t)(x[k] >> 32) == tag && (uint32_t)(y[k] >> 32) == tag;
        if (ok) break;
        if (++it > SPIN_MAX) __trap();
        __nanosleep(BACKOFF);
    }
    r0 = (__uint_as_float((uint32_t)x[0]) + __uint_as_float((uint32_t)x[1])) + (__uint_as_float((uint32_t)x[2]) + __uint_as_float((uint32_t)x[3]));
    r1 = (__uint_as_float((uint32_t)y[0]) + __uint_as_float((uint32_t)y[1])) + (__uint_as_float((uint32_t)y[2]) + __uint_as_float((uint32_t)y[3]));
}
__device__ __forceinline__ void cnt_rendezvous(unsigned* c, uint32_t target, int tsk) {
    TS(tsk);
    asm volatile("red.release.gpu.global.add.u32 [%0], 1;" ::"l"(c) : "memory");
    if (tsk == 18) TS(tsk + 1);
    uint32_t v, it = 0;
    while (true) {
        asm volatile("ld.acquire.gpu.global.u32 %0, [%1];" : "=r"(v) : "l"(c) : "memory");
        if ((int)(v - target) >= 0) break;
        if (++it > SPIN_MAX) __trap();
        __nanosleep(BACKOFF_RV);
    }
    asm volatile("fence.proxy.async.global;" ::: "memory");
}

__device__ __forceinline__ void matvec_loadA(uint32_t (&a)[8][4], uint32_t tile, uint32_t bar, int w, int lane) {
    const int i = lane >> 3, rr = lane & 7, chunk = 2 * w + (i & 1);
    const uint32_t a0 = tile + (chunk >> 3) * 8192 + (rr + 8 * (i >> 1)) * 128 + (((chunk & 7) ^ rr) << 4);
#pragma unroll
    for (int hh = 0; hh < 2; hh++) {
        mbar_wait(bar + hh * 8, 0);
#pragma unroll
        for (int k = 0; k < 4; k++) ldsm4t(a[hh * 4 + k], a0 + hh * CH + k * 2048);
    }
}
__device__ __forceinline__ void matvec_mma(float (&c)[4], const uint32_t (&a)[8][4], uint32_t vec, int nvec, int lane) {
    const uint32_t va = vec + (lane & (nvec - 1)) * VROW + (lane >> 3) * 16;
    float d[4][4];
#pragma unroll
    for (int q = 0; q < 4; q++) {
        uint32_t b[4];
        ldsm4(b, va + q * 64);
        d[q][0] = d[q][1] = d[q][2] = d[q][3] = 0.f;
        mma(d[q], a[2 * q], b[0], b[1]);
        mma(d[q], a[2 * q + 1], b[2], b[3]);
    }
#pragma unroll
    for (int k = 0; k < 4; k++) c[k] = (d[0][k] + d[1][k]) + (d[2][k] + d[3][k]);
}
__device__ __forceinline__ void matvecT(float (&c)[4], uint32_t tile, uint32_t vec, int nvec, uint32_t bar, int w, int lane) {
    uint32_t a[8][4];
    matvec_loadA(a, tile, bar, w, lane);
    matvec_mma(c, a, vec, nvec, lane);
}
template <class T> __device__ __forceinline__ T* pin(T* p) { asm volatile("" : "+l"(p)); return p; }
__device__ __forceinline__ void post(uint32_t* p, float v) {
    asm volatile("red.relaxed.gpu.global.add.u32 [%0], %1;" ::"l"(p), "r"(~__float_as_uint(v)) : "memory");
}
__device__ __forceinline__ void ld4_if(const void* p, uint4& x, bool need) {
    asm volatile("{\n.reg .pred q;\nsetp.ne.u32 q, %5, 0;\n@q ld.relaxed.gpu.global.v4.b32 {%0,%1,%2,%3}, [%4];\n}"
                 : "+r"(x.x), "+r"(x.y), "+r"(x.z), "+r"(x.w) : "l"(p), "r"((uint32_t)need) : "memory");
}
__device__ __forceinline__ void merge_store(const uint4 (&x)[5], uint32_t dst) {
#pragma unroll
    for (int b = 0; b < 2; b++) {
        const float l0 = __uint_as_float(~(b ? x[4].z : x[4].x)), l1 = __uint_as_float(~(b ? x[4].w : x[4].y));
        const float mx = fmaxf(l0, l1), e0 = ex2(l0 - mx), e1 = ex2(l1 - mx), r = rcp(e0 + e1);
        const uint4 u = x[2 * b], v = x[2 * b + 1];
        const uint32_t lo = pack2((e0 * __uint_as_float(~u.x) + e1 * __uint_as_float(~v.x)) * r, (e0 * __uint_as_float(~u.y) + e1 * __uint_as_float(~v.y)) * r);
        const uint32_t hi = pack2((e0 * __uint_as_float(~u.z) + e1 * __uint_as_float(~v.z)) * r, (e0 * __uint_as_float(~u.w) + e1 * __uint_as_float(~v.w)) * r);
        asm volatile("st.shared.v2.b32 [%0], {%1,%2};" ::"r"(dst + b * YROW), "r"(lo), "r"(hi) : "memory");
    }
}

__global__ void __launch_bounds__(NTHREADS, 1)
fused_decode_kernel(const char* __restrict__ wqraw, Scratch* const sc, const __nv_bfloat16* __restrict__ xA, const __nv_bfloat16* __restrict__ xB,
                    const char* __restrict__ Kc, const char* __restrict__ Vc, const __grid_constant__ Maps maps,
                    __nv_bfloat16* __restrict__ out, const uint32_t zero) {
    unsigned* const cnt = sc->cnt;
    asm volatile("{\n.reg .pred p;\nsetp.eq.u32 p, %1, 0;\n@p cp.async.bulk.prefetch.L2.global [%0], %2;\n}"
                 ::"l"(wqraw + (size_t)blockIdx.x * (2 * CH)), "r"(threadIdx.x), "n"(CH) : "memory");
    unsigned epoch = 0;
    asm volatile("{\n.reg .pred p;\nsetp.eq.u32 p, %2, 64;\n@p atom.relaxed.gpu.global.add.u32 %0, [%1], 1;\n}"
                 : "+r"(epoch) : "l"(cnt), "r"(threadIdx.x) : "memory");
    extern __shared__ char smem_raw[];
    const uint32_t sm = ((uint32_t)__cvta_generic_to_shared(smem_raw) + 1023u) & ~1023u;
    const uint32_t bars = sm + OFF_BAR;
    const int cta = blockIdx.x, h = cta >> 2, j = cta & 3;
    uint64_t pol = 0;
    if (threadIdx.x == 0) {
        TS(0);
        asm volatile("createpolicy.fractional.L2::evict_first.b64 %0, 1.0;" : "=l"(pol));
#pragma unroll
        for (int i = 0; i < WIN; i++) mbar_init(bars + (B_WQB + i) * 8, 1);
        asm volatile("fence.mbarrier_init.release.cluster;" ::: "memory");
#pragma unroll
        for (int i = 0; i < WIN; i++) {
            mbar_expect(bars + (B_WQB + i) * 8, CH);
            tma3d(sm + OFF_S0 + i * CH, &maps.wqB + (i >> 1), j * 128 + (i & 1) * 64, h * 2, bars + (B_WQB + i) * 8, pol);
        }
    }
    const int tid = threadIdx.x < 64 ? threadIdx.x + 384 : threadIdx.x - 64, warp = tid >> 5, lane = tid & 31;

    if (warp == 12) {
        const size_t kvoff = ((size_t)(((j >> 1) * 32 + h) * 4096 + (j & 1) * 2048)) * 256;
        const char* kp = Kc + kvoff;
        const char* vp = Vc + kvoff;
        __syncwarp();
        bar_arrive(0, NTHREADS);
        bar_sync(3, 64);
        if (lane == 0) {
            uint32_t pb[WHI];
#pragma unroll
            for (int i = 0; i < WHI; i++) pb[i] = i < WHI - WIN ? (bars + B_WO * 8) | 1u : bars + (B_WQB + i - (WHI - WIN)) * 8;
            auto pace = [&](uint32_t bar, uint32_t par) {
                uint32_t it = 0;
                while (true) {
                    const uint32_t win = ldsv(sm + OFF_WIN);
                    uint32_t busy = 0;
#pragma unroll
                    for (int i = 0; i < WHI; i++) busy += mbar_test(pb[i] & ~1u, pb[i] & 1u) ^ 1u;
                    if (busy < win) break;
                    if (++it > SPIN_MAX) __trap();
                }
#pragma unroll
                for (int i = 0; i + 1 < WHI; i++) pb[i] = pb[i + 1];
                pb[WHI - 1] = bar | par;
            };
            auto side = [&](const CUtensorMap* m, uint32_t dst, int bidx, int c1, int c2) {
                const uint32_t bar = bars + bidx * 8;
                pace(bar, 0);
                mbar_expect(bar, CH);
                tma3d(dst, m, c1, c2, bar, pol);
            };
#pragma unroll 1
            for (int i = WIN; i < 6; i++)
                side(&maps.wqB + (i >> 1), sm + OFF_S0 + i * CH, B_WQB + i, j * 128 + (i & 1) * 64, h * 2);
            TS(1);
            uint32_t slot = 0, use = 0;
            int nuv = 0;
#pragma unroll 1
            for (int n = 0; n < 2 * NTILE; n++) {
                if (n == RING) {
                    mbar_wait(bars + B_FREE * 8, 0);
#pragma unroll 1
                    for (int q = 0; q < 4; q++) side(&maps.ckv, sm + OFF_S0 + q * CH, B_CKV + q, cta * 64 + q * 16, 0);
                }
                if (nuv < 2 && n > RING && (n >= 2 * NTILE - 8 || mbar_test(bars + B_FREE * 8, 1))) {
                    mbar_wait(bars + B_FREE * 8, 1);
                    side(&maps.wuv, sm + OFF_S1 + nuv * CH, B_WUV + nuv, j * 128 + nuv * 64, h * 2);
                    nuv++;
                }
                const uint32_t fb = bars + slot * 8;
                pace(fb, use & 1);
                mbar_wait(fb + B_EMPTY * 8, (use & 1) ^ 1);
                mbar_expect(fb, CH);
                bulk1d(sm + OFF_RING + slot * CH, ((n & 1) ? vp : kp) + (size_t)(n >> 1) * CH, fb, pol);
                if (n >= FINE_V || (n & 1)) {
                    asm volatile("red.relaxed.gpu.global.add.u32 [%0], %1;" ::"l"(cnt + 3), "r"(n >= FINE_V ? 1 : 2) : "memory");
                    stsv(sm + OFF_NOW, n + 1);
                }
                if (++slot == RING) { slot = 0; use++; }
            }
            TS(2);
            mbar_wait(bars + B_FREE * 8, 0);
            uint32_t it = 0;
#pragma unroll 1
            for (int q = 0; q < 8; q++) {
                const uint32_t bar = bars + (B_WO + q) * 8;
                mbar_expect(bar, CH / 2);
                while (true) {
                    const uint32_t t0 = ldsv(sm + OFF_TBOX);
                    if (t0 && gtime() - t0 + 16384u >= 16384u + q * BOX_NS) break;
                    if (++it > SPIN_MAX) __trap();
                }
                tma3d(sm + OFF_S0 + q * (CH / 2), &maps.woA + (cta & 1), (cta >> 4) * 512 + q * 64, (cta >> 1) & 7, bar, pol);
            }
            TS(3);
        }
    } else if (warp == 13) {
        if (lane == 0) {
#pragma unroll
            for (int i = 0; i < NBAR; i++)
                if (i < B_WQB || i >= B_WQB + WIN)
                    mbar_init(bars + i * 8, i == B_FREE ? 8 : (i >= B_EMPTY && i < B_EMPTY + RING) ? 4 : 1);
            asm volatile("fence.mbarrier_init.release.cluster;" ::: "memory");
#pragma unroll
            for (int i = 2; i < 8; i++) asm volatile("prefetch.tensormap [%0];" ::"l"(&maps.wqB + i) : "memory");
            stsv(sm + OFF_NOW, 0); stsv(sm + OFF_WIN, WIN); stsv(sm + OFF_TBOX, 0);
        }
        __syncwarp();
        bar_arrive(3, 64);
        bar_sync(0, NTHREADS);
        if (lane == 0) {
            const uint32_t base = (lds32(sm + OFF_TAG) - 1u) * (NCTA * 2 * NTILE);
            mbar_wait(bars + (B_WUK + 1) * 8, 0);
            uint32_t it = 0, tbox = 0;
            while (true) {
                const uint32_t n = ldsv(sm + OFF_NOW);
                uint32_t v;
                asm volatile("ld.relaxed.gpu.global.u32 %0, [%1];" : "=r"(v) : "l"(cnt + 3) : "memory");
                v -= base;
                if (v >= NCTA * EST_FROM && (v <= NCTA * EST_TO || !tbox)) {
                    const uint32_t est = (gtime() + (NCTA * 2 * NTILE - v) * BOX_NS / 64 + (uint32_t)(BOX_SHIFT + (cta * 37 & 127) * BOX_SPREAD / 128)) | 1u;
                    if (!tbox || (int)(est - tbox) < 0) { tbox = est; stsv(sm + OFF_TBOX, est); }
                }
                if (v >= NCTA * 2 * NTILE - GATE_W) break;
                const int diff = (int)(n * NCTA) - (int)v;
                stsv(sm + OFF_WIN, diff < -THETA ? WHI : WIN - (diff > THETA) - (v >= NCTA * END_V));
                if (++it > SPIN_MAX) __trap();
                __nanosleep(v < NCTA * FINE_V ? BACKOFF3 : BACKOFF2);
            }
            stsv(sm + OFF_WIN, WHI);
            TS(24);
        }
    } else if (warp < 4) {
        const int g = lane >> 2, t = lane & 3, i = lane >> 3, rr = lane & 7;
        if (tid == 0) sts32(sm + OFF_TAG, (epoch >> 7) + 1u);
        bar_sync(0, NTHREADS);
        const uint32_t tag = lds32(sm + OFF_TAG);
        {
            mbar_wait(bars + 8, 0);
            float q0, q1;
            ll_gather4(&sc->e1[0][h * 4][tid], tag, q0, q1);
            sts16(sm + OFF_QB + tid * 2, f2bf((j >> 1) ? q1 : q0));
        }
        bar_sync(1, 128);
        if (tid == 0) TS(4);
        uint32_t qf[8][2];
#pragma unroll
        for (int c = 0; c < 8; c++) {
            const uint32_t a = sm + OFF_QB + (((c + g) & 7) * 8 + 2 * t) * 2;
            qf[c][0] = lds32(a); qf[c][1] = lds32(a + 128);
        }
        float acc[8][4];
#pragma unroll
        for (int c = 0; c < 8; c++) { acc[c][0] = acc[c][1] = acc[c][2] = acc[c][3] = 0.f; }
        float m = -INFINITY, l = 0.f;
        const bool diag = (t == (g >> 1));
        const uint32_t krow = sm + OFF_RING + (warp * 16 + rr + 8 * (i & 1)) * 256 + (i >> 1) * 128;
        const uint32_t vrow = sm + OFF_RING + (warp * 16 + rr + 8 * (i >> 1)) * 256 + (i & 1) * 128;
        uint32_t slot = 0, ph = 0;
        uint32_t* const e5own = pin(&sc->e5[cta][tid]);
        uint32_t a[8][4], b0, b1;
#pragma unroll 1
        for (int tile = 0;; tile++) {
            mbar_wait(bars + slot * 8, ph);
#pragma unroll
            for (int c = 0; c < 8; c++) ldsm4(a[c], krow + slot * CH + (((c + rr) & 7) << 4));
            __syncwarp();
            if (lane == 0) mbar_arrive(bars + (B_EMPTY + slot) * 8 + ((a[0][0] | a[1][0] | a[2][0] | a[3][0] | a[4][0] | a[5][0] | a[6][0] | a[7][0]) & zero));
            if (++slot == RING) { slot = 0; ph ^= 1; }
            float s0[4] = {0.f, 0.f, 0.f, 0.f}, s1[4] = {0.f, 0.f, 0.f, 0.f};
#pragma unroll
            for (int c = 0; c < 8; c += 2) { mma(s0, a[c], qf[c][0], qf[c][1]); mma(s1, a[c + 1], qf[c + 1][0], qf[c + 1][1]); }
            float slo = (g & 1) ? s0[1] + s1[1] : s0[0] + s1[0];
            float shi = (g & 1) ? s0[3] + s1[3] : s0[2] + s1[2];
            slo = diag ? bfround(bfround(slo) * SCALE) : -INFINITY;
            shi = diag ? bfround(bfround(shi) * SCALE) : -INFINITY;
            int key = __float_as_int(fmaxf(slo, shi));
            key ^= (key >> 31) & 0x7fffffff;
            key = __reduce_max_sync(0xffffffffu, key);
            key ^= (key >> 31) & 0x7fffffff;
            const float mn = fmaxf(m, __int_as_float(key));
            const float alpha = ex2((m - mn) * LOG2E);
            m = mn;
            const float plo = ex2((slo - mn) * LOG2E), phi = ex2((shi - mn) * LOG2E);
            l = l * alpha + (plo + phi);
            b0 = (g & 1) ? pack2(0.f, plo) : pack2(plo, 0.f);
            b1 = (g & 1) ? pack2(0.f, phi) : pack2(phi, 0.f);
#pragma unroll
            for (int c = 0; c < 8; c++) { acc[c][0] *= alpha; acc[c][1] *= alpha; acc[c][2] *= alpha; acc[c][3] *= alpha; }
            if (tile == NTILE - 1) break;
            mbar_wait(bars + slot * 8, ph);
#pragma unroll
            for (int c = 0; c < 8; c++) ldsm4t(a[c], vrow + slot * CH + (((c + rr) & 7) << 4));
            __syncwarp();
            if (lane == 0) mbar_arrive(bars + (B_EMPTY + slot) * 8 + ((a[0][0] | a[1][0] | a[2][0] | a[3][0] | a[4][0] | a[5][0] | a[6][0] | a[7][0]) & zero));
            if (++slot == RING) { slot = 0; ph ^= 1; }
#pragma unroll
            for (int c = 0; c < 8; c++) mma(acc[c], a[c], b0, b1);
        }
#pragma unroll
        for (int o = 16; o; o >>= 1) l += __shfl_xor_sync(0xffffffffu, l, o);
        if (lane == 0) stsf2(sm + OFF_ML + warp * 8, m, l);
        mbar_wait(bars + B_S2 * 8, 0);
        bar_sync(1, 128);
        {
            const uint4 ml0 = lds128(sm + OFF_ML), ml1 = lds128(sm + OFF_ML + 16);
            const float m0 = __uint_as_float(ml0.x), m1 = __uint_as_float(ml0.z), m2 = __uint_as_float(ml1.x), m3 = __uint_as_float(ml1.z);
            const float M = fmaxf(fmaxf(m0, m1), fmaxf(m2, m3));
            const float L = (ex2((m0 - M) * LOG2E) * __uint_as_float(ml0.y) + ex2((m1 - M) * LOG2E) * __uint_as_float(ml0.w))
                          + (ex2((m2 - M) * LOG2E) * __uint_as_float(ml1.y) + ex2((m3 - M) * LOG2E) * __uint_as_float(ml1.w));
            const float f = ex2((m - M) * LOG2E) * rcp(L);
            if (tid == 0) post(e5own + (NCTA - cta) * 128 + cta, M * LOG2E + lg2(L));
            mbar_wait(bars + slot * 8, ph);
#pragma unroll
            for (int c = 0; c < 8; c++) ldsm4t(a[c], vrow + slot * CH + (((c + rr) & 7) << 4));
#pragma unroll
            for (int c = 0; c < 8; c++) mma(acc[c], a[c], b0, b1);
            if (tid == 0) TS(5);
            float v[2][8];
#pragma unroll
            for (int c = 0; c < 8; c++) { v[0][c] = acc[c][0] + acc[(c + 7) & 7][1]; v[1][c] = acc[c][2] + acc[(c + 7) & 7][3]; }
#pragma unroll
            for (int c = 0; c < 4; c++) { v[0][c] += __shfl_xor_sync(0xffffffffu, v[0][c + 4], 2); v[1][c] += __shfl_xor_sync(0xffffffffu, v[1][c + 4], 2); }
            const int src = (lane & ~3) | ((lane + 3) & 3);
#pragma unroll
            for (int c = 0; c < 2; c++) { v[0][c] += __shfl_sync(0xffffffffu, v[0][c + 2], src); v[1][c] += __shfl_sync(0xffffffffu, v[1][c + 2], src); }
            const uint32_t wa = sm + OFF_S2 + (warp * 160 + 16 * t + 8 * (t >> 1) + g) * 4;
            sts32(wa, __float_as_uint(v[0][0] * f)); sts32(wa + 32, __float_as_uint(v[0][1] * f));
            sts32(wa + 320, __float_as_uint(v[1][0] * f)); sts32(wa + 352, __float_as_uint(v[1][1] * f));
            bar_sync(1, 128);
            const uint32_t ra = sm + OFF_S2 + (tid + warp * 8) * 4;
            post(e5own, (ldsf(ra) + ldsf(ra + 640)) + (ldsf(ra + 1280) + ldsf(ra + 1920)));
        }
        if (tid == 0) TS(6);
        if (cta & 1) {
            const int c0 = (cta & ~15) + warp * 4;
            const uint32_t* p = e5own + ((c0 - cta) * 128 + lane * 4 - tid);
            const uint32_t* pl = e5own + ((NCTA - cta) * 128 + c0 - tid);
            uint4 x[5];
            bool need[5] = {true, true, true, true, true};
            uint32_t it = 0;
            while (true) {
#pragma unroll
                for (int q = 0; q < 5; q++) ld4_if(q < 4 ? p + q * 128 : pl, x[q], need[q]);
#pragma unroll
                for (int q = 0; q < 5; q++) need[q] = !x[q].x || !x[q].y || !x[q].z || !x[q].w;
                if (!__any_sync(0xffffffffu, need[0] | need[1] | need[2] | need[3] | need[4])) break;
                if (++it > SPIN_MAX) __trap();
            }
            merge_store(x, sm + OFF_Y + warp * YHEAD + lane * 8);
            bar_arrive(4, 256 + 128);
        }
        if (tid == 0) TS(16);
    } else {
        const int st = tid - 128, w = warp - 4;
        const int g = lane >> 2, t = lane & 3, i = lane >> 3, rr = lane & 7;
        if (st < 64) {
            const int which = st >> 5, b = (st >> 4) & 1, c = st & 15;
            const uint4 v = __ldg((const uint4*)((which ? xA : xB) + b * 512 + j * 128) + c);
            sts128(sm + OFF_XB + (which * 2 + b) * VROW + c * 16, v);
        }
        bar_sync(0, NTHREADS);
        const uint32_t tag = lds32(sm + OFF_TAG);
        float c[4];
#pragma unroll 1
        for (int which = 0; which < 2; which++) {
            matvecT(c, sm + OFF_S0 + which * 2 * CH, sm + OFF_XB + which * 2 * VROW, 2, bars + (B_WQB + which * 2) * 8, w, lane);
            if (t == 0) {
                ll_store2(&sc->e1[which][cta][w * 16 + g], c[0], c[1], tag);
                ll_store2(&sc->e1[which][cta][w * 16 + g + 8], c[2], c[3], tag);
            }
        }
        __syncwarp();
        if (lane == 0) mbar_arrive(bars + B_FREE * 8);
        if (st == 0) TS(8);
        if (st < 128) {
            float q0, q1;
            sleep_ns(POLL_DELAY);
            ll_gather4(&sc->e1[1][h * 4][st], tag, q0, q1);
            sts16(sm + OFF_QA + st * 2, f2bf(q0)); sts16(sm + OFF_QA + VROW + st * 2, f2bf(q1));
        }
        bar_sync(2, 256);
        if (st == 0) TS(9);
        {
            const int row = w * 16 + rr + 8 * (i & 1);
            const uint32_t a0 = sm + OFF_S2 + (row >> 6) * CH + (row & 63) * 128;
            const uint32_t va = sm + OFF_QA + g * VROW + t * 4;
            float d[4] = {0.f, 0.f, 0.f, 0.f};
            c[0] = c[1] = c[2] = c[3] = 0.f;
            mbar_wait(bars + (B_WUK + (w >> 2)) * 8, 0);
#pragma unroll
            for (int ks = 0; ks < 8; ks++) {
                const int chunk = 2 * ks + (i >> 1);
                uint32_t a[4];
                ldsm4(a, a0 + (chunk >> 3) * 8192 + (((chunk & 7) ^ rr) << 4));
                const uint32_t b0 = (g < 2) ? lds32(va + ks * 32) : 0u, b1 = (g < 2) ? lds32(va + ks * 32 + 16) : 0u;
                if (ks & 1) mma(d, a, b0, b1); else mma(c, a, b0, b1);
            }
            if (t == 0) {
                const uint32_t qs = sm + OFF_QS + (w * 16 + g) * 2;
                sts16(qs, f2bf(c[0] + d[0])); sts16(qs + VROW, f2bf(c[1] + d[1]));
                sts16(qs + 16, f2bf(c[2] + d[2])); sts16(qs + VROW + 16, f2bf(c[3] + d[3]));
            }
            bar_sync(2, 256);
            if (w == 0) {
                const int b = lane >> 4, cc = lane & 15;
                sc->qabs[(b * 32 + h) * 64 + ((j * 16 + cc) ^ (h & 7))] = lds128(sm + OFF_QS + b * VROW + cc * 16);
                __syncwarp();
                if (lane == 0) {
                    cnt_rendezvous(cnt + 1, tag * 128u, 18);
                    TS(10);
                    mbar_expect(bars + B_GATH * 8, 2 * CH);
                    bulk1d_n(sm + OFF_S2, sc->qabs + (cta >> 6) * 2048, 2 * CH, bars + B_GATH * 8);
                }
                __syncwarp();
            }
        }
        mbar_wait(bars + B_GATH * 8, 0);
        if (st == 0) TS(11);
        {
            const int mt = w & 1, kg = w >> 1;
            const uint32_t qa = sm + OFF_S2 + (mt * 16 + rr + 8 * (i & 1)) * 1024;
            const uint32_t ka = sm + OFF_S0 + kg * CH + (rr + 8 * (i >> 1)) * 128;
            float s0[4] = {0.f, 0.f, 0.f, 0.f}, s1[4] = {0.f, 0.f, 0.f, 0.f};
            mbar_wait(bars + (B_CKV + kg) * 8, 0);
#pragma unroll 2
            for (int gq = 0; gq < 8; gq++) {
#pragma unroll
                for (int k4 = 0; k4 < 4; k4++) {
                    uint32_t a[4], b[4];
                    ldsm4(a, qa + gq * 128 + (((2 * k4 + (i >> 1)) ^ rr) << 4));
                    ldsm4(b, ka + gq * 2048 + (((2 * k4 + (i & 1)) ^ rr) << 4));
                    mma(s0, a, b[0], b[1]);
                    mma(s1, a, b[2], b[3]);
                }
            }
            const uint32_t sa = sm + OFF_SC + ((mt * 16 + g) * 68 + kg * 16 + 2 * t) * 4;
            stsf2(sa, s0[0], s0[1]); stsf2(sa + 32, s1[0], s1[1]);
            stsf2(sa + 8 * 68 * 4, s0[2], s0[3]); stsf2(sa + 8 * 68 * 4 + 32, s1[2], s1[3]);
        }
        bar_sync(2, 256);
        {
            const int head = w * 4 + i;
            const uint32_t sa = sm + OFF_SC + (head * 68 + rr * 8) * 4;
            const uint4 u0 = lds128(sa), u1 = lds128(sa + 16);
            float s[8] = {__uint_as_float(u0.x), __uint_as_float(u0.y), __uint_as_float(u0.z), __uint_as_float(u0.w),
                          __uint_as_float(u1.x), __uint_as_float(u1.y), __uint_as_float(u1.z), __uint_as_float(u1.w)};
            float mx = s[0];
#pragma unroll
            for (int k = 1; k < 8; k++) mx = fmaxf(mx, s[k]);
#pragma unroll
            for (int o = 1; o < 8; o <<= 1) mx = fmaxf(mx, __shfl_xor_sync(0xffffffffu, mx, o));
            float sum = 0.f;
#pragma unroll
            for (int k = 0; k < 8; k++) { s[k] = ex2((s[k] - mx) * (SCALE * LOG2E)); sum += s[k]; }
#pragma unroll
            for (int o = 1; o < 8; o <<= 1) sum += __shfl_xor_sync(0xffffffffu, sum, o);
            const float inv = __fdividef(1.f, sum);
            uint4 p;
            p.x = pack2(s[0] * inv, s[1] * inv); p.y = pack2(s[2] * inv, s[3] * inv);
            p.z = pack2(s[4] * inv, s[5] * inv); p.w = pack2(s[6] * inv, s[7] * inv);
            sts128(sm + OFF_P + head * 128 + ((rr ^ (head & 7)) << 4), p);
            if (rr == 0) ((float*)sc->lse)[head * 128 + cta] = mx * (SCALE * LOG2E) + lg2(sum);
        }
        bar_sync(2, 256);
        {
            float o[2][8][4];
#pragma unroll
            for (int mt = 0; mt < 2; mt++)
#pragma unroll
                for (int n = 0; n < 8; n++) { o[mt][n][0] = o[mt][n][1] = o[mt][n][2] = o[mt][n][3] = 0.f; }
            const uint32_t pa = sm + OFF_P + (rr + 8 * (i & 1)) * 128;
            const uint32_t va = sm + OFF_S0 + w * 2048 + (rr + 8 * (i & 1)) * 128;
#pragma unroll 1
            for (int kq = 0; kq < 4; kq++) {
                uint32_t a0[4], a1[4];
                ldsm4(a0, pa + (((2 * kq + (i >> 1)) ^ rr) << 4));
                ldsm4(a1, pa + 2048 + (((2 * kq + (i >> 1)) ^ rr) << 4));
#pragma unroll
                for (int n = 0; n < 8; n += 2) {
                    uint32_t b[4];
                    ldsm4t(b, va + kq * CH + (((n + (i >> 1)) ^ rr) << 4));
                    mma(o[0][n], a0, b[0], b[1]); mma(o[1][n], a1, b[0], b[1]);
                    mma(o[0][n + 1], a0, b[2], b[3]); mma(o[1][n + 1], a1, b[2], b[3]);
                }
            }
#pragma unroll
            for (int mt = 0; mt < 2; mt++)
#pragma unroll
                for (int hf = 0; hf < 2; hf++) {
                    const uint32_t dst = sm + OFF_S2 + (mt * 16 + hf * 8 + g) * 1024 + w * 128 + t * 16;
#pragma unroll
                    for (int nb = 0; nb < 2; nb++) {
                        uint4 v;
                        v.x = pack2(o[mt][nb * 4 + 0][hf * 2], o[mt][nb * 4 + 0][hf * 2 + 1]);
                        v.y = pack2(o[mt][nb * 4 + 1][hf * 2], o[mt][nb * 4 + 1][hf * 2 + 1]);
                        v.z = pack2(o[mt][nb * 4 + 2][hf * 2], o[mt][nb * 4 + 2][hf * 2 + 1]);
                        v.w = pack2(o[mt][nb * 4 + 3][hf * 2], o[mt][nb * 4 + 3][hf * 2 + 1]);
                        sts128(dst + nb * 64, v);
                    }
                }
            asm volatile("fence.proxy.async.shared::cta;" ::: "memory");
            __syncwarp();
            if (lane == 0) mbar_arrive(bars + B_FREE * 8);
            sc->e4[cta][st] = 0u;
            if (st < 128) sc->e5[cta][st] = 0u;
            else if (cta == 0) sc->e5[NCTA][st - 128] = 0u;
            if (st >= 248) ((uint32_t*)out)[cta * 8 + st - 248] = 0u;
        }
        bar_sync(2, 256);
        if (st == 0) {
            TS(12);
#pragma unroll 1
            for (int k = 0; k < ST_SPLIT; k++) {
                asm volatile("cp.async.bulk.tensor.3d.global.shared::cta.bulk_group [%0, {%2,%3,%4}], [%1];"
                             ::"l"(&maps.ctxp), "r"(sm + OFF_S2 + k * (2 * CH / ST_SPLIT)), "r"(0), "r"(cta), "r"(k * (128 / ST_SPLIT)) : "memory");
                if (k + 1 < ST_SPLIT) __nanosleep(ST_GAP);
            }
            asm volatile("cp.async.bulk.commit_group;" ::: "memory");
            asm volatile("cp.async.bulk.wait_group 0;" ::: "memory");
            cnt_rendezvous(cnt + 2, tag * 128u, 20);
            TS(13);
            mbar_expect(bars + B_GATH * 8, 2 * CH + 512);
            bulk1d_n(sm + OFF_LSE, sc->lse + h * 32, 512, bars + B_GATH * 8);
#pragma unroll 1
            for (int k = 0; k < ST_SPLIT; k++) {
                bulk1d_n(sm + OFF_S2 + k * (2 * CH / ST_SPLIT), sc->ctxp + cta * 2048 + k * (2048 / ST_SPLIT), 2 * CH / ST_SPLIT, bars + B_GATH * 8);
                __nanosleep(LD_GAP);
            }
        }
        __syncwarp();
        {
            mbar_wait(bars + B_GATH * 8, 1);
            if (st == 0) TS(22);
            uint4 v[8];
#pragma unroll
            for (int k = 0; k < 8; k++) v[k] = lds128(sm + OFF_S2 + (k * 256 + st) * 16);
            float ls[4];
#pragma unroll
            for (int k = 0; k < 4; k++) ls[k] = ldsf(sm + OFF_LSE + (k * 32 + lane) * 4);
            float m0 = fmaxf(ls[0], ls[1]), m1 = fmaxf(ls[2], ls[3]);
#pragma unroll
            for (int o = 16; o; o >>= 1) { m0 = fmaxf(m0, __shfl_xor_sync(0xffffffffu, m0, o)); m1 = fmaxf(m1, __shfl_xor_sync(0xffffffffu, m1, o)); }
            ls[0] = ex2(ls[0] - m0); ls[1] = ex2(ls[1] - m0); ls[2] = ex2(ls[2] - m1); ls[3] = ex2(ls[3] - m1);
            float z0 = ls[0] + ls[1], z1 = ls[2] + ls[3];
#pragma unroll
            for (int o = 16; o; o >>= 1) { z0 += __shfl_xor_sync(0xffffffffu, z0, o); z1 += __shfl_xor_sync(0xffffffffu, z1, o); }
            z0 = __fdividef(1.f, z0); z1 = __fdividef(1.f, z1);
            ls[0] *= z0; ls[1] *= z0; ls[2] *= z1; ls[3] *= z1;
            float a[2][8];
#pragma unroll
            for (int e = 0; e < 8; e++) a[0][e] = a[1][e] = 0.f;
            const int rg = st >> 4;
#pragma unroll
            for (int k = 0; k < 8; k++) {
                const float wt = __shfl_sync(0xffffffffu, ls[k >> 1], rg + 16 * (k & 1));
                const uint32_t u[4] = {v[k].x, v[k].y, v[k].z, v[k].w};
#pragma unroll
                for (int e = 0; e < 4; e++) {
                    a[k >> 2][2 * e] += wt * __uint_as_float(u[e] << 16);
                    a[k >> 2][2 * e + 1] += wt * __uint_as_float(u[e] & 0xffff0000u);
                }
            }
            const int b = lane >> 4, u16 = lane & 15;
            const uint32_t ra = sm + OFF_SC + (w * 256 + b * 128 + (u16 >> 3) * 64 + ((u16 >> 2) & 1) * 32 + (u16 & 3) * 2) * 4;
#pragma unroll
            for (int e = 0; e < 8; e += 2) {
                const float k0 = b ? a[1][e] : a[0][e], k1 = b ? a[1][e + 1] : a[0][e + 1];
                const float s0 = b ? a[0][e] : a[1][e], s1 = b ? a[0][e + 1] : a[1][e + 1];
                stsf2(ra + (e >> 1) * 32, k0 + __shfl_xor_sync(0xffffffffu, s0, 16), k1 + __shfl_xor_sync(0xffffffffu, s1, 16));
            }
            bar_sync(2, 256);
            if (st == 0) mbar_arrive(bars + B_S2 * 8);
            float s = 0.f;
#pragma unroll
            for (int k = 0; k < 8; k++) s += ldsf(sm + OFF_SC + (k * 256 + st) * 4);
            const float hi = bfround(s);
            const uint32_t ca = sm + OFF_CC + (st >> 7) * VROW + (st & 127) * 2;
            sts16(ca, f2bf(hi)); sts16(ca + 2 * VROW, f2bf(s - hi));
            bar_sync(2, 256);
        }
        matvecT(c, sm + OFF_S1, sm + OFF_CC, 4, bars + B_WUV * 8, w, lane);
#pragma unroll
        for (int k = 0; k < 4; k++) c[k] += __shfl_xor_sync(0xffffffffu, c[k], 1);
        post(&sc->e4[cta][(t & 1) * 128 + w * 16 + (t >> 1) * 8 + g], t == 0 ? c[0] : t == 1 ? c[1] : t == 2 ? c[2] : c[3]);
        __syncwarp();
        if (lane == 0) mbar_arrive(bars + B_FREE * 8);
        if (st == 0) TS(23);
        if (st < 128) sts32(sm + OFF_PAIR + st * 4, EMPTY);
        if (!(cta & 1)) {
            const uint32_t* p = &sc->e4[(cta & ~15) + (w >> 1) * 4][(w & 1) * 128 + lane * 4];
            uint4 x[4];
            bool need[4] = {true, true, true, true};
            uint32_t it = 0;
            sleep_ns(POLL_DELAY2);
            while (true) {
#pragma unroll
                for (int q = 0; q < 4; q++) ld4_if(p + q * 256, x[q], need[q]);
#pragma unroll
                for (int q = 0; q < 4; q++) need[q] = !x[q].x || !x[q].y || !x[q].z || !x[q].w;
                if (!__any_sync(0xffffffffu, need[0] | need[1] | need[2] | need[3])) break;
                if (++it > SPIN_MAX) __trap();
                __nanosleep(BACKOFF);
            }
            auto sum4 = [](uint32_t a, uint32_t b, uint32_t c, uint32_t d) {
                return (__uint_as_float(~a) + __uint_as_float(~b)) + (__uint_as_float(~c) + __uint_as_float(~d));
            };
            asm volatile("st.shared.v2.b32 [%0], {%1,%2};" ::"r"(sm + OFF_Y + (w & 1) * YROW + (w >> 1) * YHEAD + lane * 8),
                         "r"(pack2(sum4(x[0].x, x[1].x, x[2].x, x[3].x), sum4(x[0].y, x[1].y, x[2].y, x[3].y))),
                         "r"(pack2(sum4(x[0].z, x[1].z, x[2].z, x[3].z), sum4(x[0].w, x[1].w, x[2].w, x[3].w))) : "memory");
        }
        if (st == 0) TS(14);
        bar_sync(2, 256);
        {
            const int hf = w >> 2, cg = w & 3;
            const uint32_t a0 = sm + OFF_S0 + hf * 8192 + (rr + 8 * (i >> 1)) * 128 + (((2 * cg + (i & 1)) ^ rr) << 4);
            const uint32_t va = sm + OFF_Y + (lane >> 1 & 1) * YROW + (lane & 1) * YHEAD + hf * 128 + i * 16;
            const uint32_t wb = bars + (B_WO + hf) * 8;
            const uint32_t pa = sm + OFF_PAIR + (cg * 32 + lane) * 4;
            const int col = (t & 1) * 1024 + (cta & 1) * 512 + (cta >> 1 & 7) * 64 + cg * 16 + (t >> 1) * 8 + g;
            __nv_bfloat16* const outp = pin(out + (col & ~1));
            const bool up = t >= 2, odd = g & 1;
            uint32_t a[4][4][4], b[4][4];
            float d[2][4][4];
#pragma unroll
            for (int k = 0; k < 8; k++) d[k >> 2][k & 3][0] = d[k >> 2][k & 3][1] = d[k >> 2][k & 3][2] = d[k >> 2][k & 3][3] = 0.f;
            auto load_w = [&](int hd) {
                mbar_wait(wb + hd * 16, 0);
#pragma unroll
                for (int k = 0; k < 4; k++) ldsm4t(a[hd][k], a0 + hd * CH + k * 2048);
            };
            auto load_y = [&]() {
#pragma unroll
                for (int q = 0; q < 4; q++) ldsm4(b[q], va + (q >> 1) * 2 * YHEAD + (q & 1) * 64);
            };
            auto head = [&](int hd) {
#pragma unroll
                for (int k = 0; k < 4; k++) mma(d[hd & 1][k], a[hd][k], b[(hd & 2) + (k >> 1)][(k & 1) * 2], b[(hd & 2) + (k >> 1)][(k & 1) * 2 + 1]);
            };
            if (cta & 1) {
                load_w(0); load_w(1);
                bar_sync(4, 256 + 128);
                load_y();
                head(0); head(1);
            } else {
                load_y();
                load_w(0); head(0);
                load_w(1); head(1);
            }
            if (st == 0) TS(25);
            load_w(2); head(2);
            float z = up ? (d[0][0][2] + d[0][1][2]) + (d[0][2][2] + d[0][3][2]) : (d[0][0][0] + d[0][1][0]) + (d[0][2][0] + d[0][3][0]);
            mbar_wait_uni(wb + 48);
            if (st == 0) TS(26);
            uint32_t other = ldsv(pa);
#pragma unroll
            for (int k = 0; k < 4; k++) ldsm4t(a[3][k], a0 + 3 * CH + k * 2048);
            head(3);
            z += other != EMPTY ? __uint_as_float(other) : 0.f;
            float z1 = z, z3 = z;
#pragma unroll
            for (int k = 0; k < 3; k++) { z1 += d[1][k][1]; z3 += d[1][k][3]; }
            z = up ? z3 + d[1][3][3] : z1 + d[1][3][1];
            if (st == 0) TS(17);
            asm volatile("{\n.reg .pred p;\nsetp.eq.u32 p, %2, %3;\n@p bra FIRST;\nred.relaxed.gpu.global.add.noftz.bf16x2 [%0], %1;\nexit;\nFIRST:\n}"
                         ::"l"(outp), "r"(odd ? pack2(0.f, z) : pack2(z, 0.f)), "r"(other), "n"(EMPTY) : "memory");
            asm volatile("atom.shared.exch.b32 %0, [%1], %2;" : "=r"(other) : "r"(pa), "r"(__float_as_uint(z)) : "memory");
            z += __uint_as_float(other);
            asm volatile("{\n.reg .pred p;\nsetp.eq.u32 p, %2, %3;\n@p exit;\nred.relaxed.gpu.global.add.noftz.bf16x2 [%0], %1;\n}"
                         ::"l"(outp), "r"(odd ? pack2(0.f, z) : pack2(z, 0.f)), "r"(other), "n"(EMPTY) : "memory");
        }
    }
}

typedef CUresult (*EncodeFn)(CUtensorMap*, CUtensorMapDataType, cuuint32_t, void*, const cuuint64_t*, const cuuint64_t*,
                             const cuuint32_t*, const cuuint32_t*, CUtensorMapInterleave, CUtensorMapSwizzle,
                             CUtensorMapL2promotion, CUtensorMapFloatOOBfill);

void make_map(EncodeFn enc, CUtensorMap* m, void* p, unsigned rows, unsigned cols, unsigned br, unsigned bg) {
    cuuint64_t gd[3] = {64, rows, cols / 64};
    cuuint64_t gs[2] = {(cuuint64_t)cols * 2, 128};
    cuuint32_t bx[3] = {64, br, bg};
    cuuint32_t es[3] = {1, 1, 1};
    enc(m, CU_TENSOR_MAP_DATA_TYPE_BFLOAT16, 3, p, gd, gs, bx, es, CU_TENSOR_MAP_INTERLEAVE_NONE,
        CU_TENSOR_MAP_SWIZZLE_128B, CU_TENSOR_MAP_L2_PROMOTION_L2_128B, CU_TENSOR_MAP_FLOAT_OOB_FILL_NONE);
}

}

extern "C" void kernel_launch(void* const* d_in, const int* in_sizes, int n_in, void* d_out, int out_size) {
    static EncodeFn enc = nullptr;
    if (!enc) {
        void* fn = nullptr;
        cudaDriverEntryPointQueryResult qr;
        cudaGetDriverEntryPoint("cuTensorMapEncodeTiled", &fn, cudaEnableDefault, &qr);
        enc = (EncodeFn)fn;
        cudaFuncSetAttribute(fused_decode_kernel, cudaFuncAttributeMaxDynamicSharedMemorySize, SMEM_BYTES);
    }
    Scratch* sc = nullptr;
    cudaGetSymbolAddress((void**)&sc, g_scratch);
    Maps maps;
    make_map(enc, &maps.wqB, d_in[9], 512, 4096, 64, 2);
    make_map(enc, &maps.wqA, d_in[2], 512, 4096, 64, 2);
    make_map(enc, &maps.wuk, d_in[3], 512, 4096, 64, 2);
    make_map(enc, &maps.wuv, d_in[4], 512, 4096, 64, 2);
    make_map(enc, &maps.woA, d_in[5], 4096, 512, 64, 1);
    make_map(enc, &maps.woB, d_in[10], 4096, 512, 64, 1);
    make_map(enc, &maps.ckv, d_in[1], 8192, 512, 16, 8);
    {
        void* p = sc->ctxp;
        cuuint64_t gd[3] = {128, 128, 128};
        cuuint64_t gs[2] = {256, 32768};
        cuuint32_t bx[3] = {128, 1, 128 / ST_SPLIT};
        cuuint32_t es[3] = {1, 1, 1};
        enc(&maps.ctxp, CU_TENSOR_MAP_DATA_TYPE_BFLOAT16, 3, p, gd, gs, bx, es, CU_TENSOR_MAP_INTERLEAVE_NONE,
            CU_TENSOR_MAP_SWIZZLE_NONE, CU_TENSOR_MAP_L2_PROMOTION_NONE, CU_TENSOR_MAP_FLOAT_OOB_FILL_NONE);
    }
    fused_decode_kernel<<<NCTA, NTHREADS, SMEM_BYTES>>>((const char*)d_in[9], sc, (const __nv_bfloat16*)d_in[0], (const __nv_bfloat16*)d_in[6],
                                                         (const char*)d_in[7], (const char*)d_in[8], maps, (__nv_bfloat16*)d_out, 0u);
}
```

```cpp
#include <cuda_runtime.h>
#include <cuda.h>
#include <cuda_bf16.h>
#include <stdint.h>

#define RING 7
#define WIN 4
#define WHI 5
#define THETA 64
#define END_V 40
#define GATE_W 64
#define BOX_NS 319
#define BOX_SHIFT 5
#define BOX_SPREAD 150
#define EST_FROM 57
#define EST_TO 62
#define POLL_DELAY 3000
#define POLL_DELAY2 2500
#define ST_SPLIT 8
#define ST_GAP 500
#define LD_GAP 300
#define BACKOFF 200
#define BACKOFF_RV 800
#define FINE_V 52
#define BACKOFF2 100
#define BACKOFF3 300

namespace {

constexpr int NCTA = 128;
constexpr int NTHREADS = 448;
constexpr uint32_t CH = 16384;
constexpr int NTILE = 32;

constexpr uint32_t OFF_RING = 0;
constexpr uint32_t OFF_S0 = RING * CH;
constexpr uint32_t OFF_S1 = OFF_S0 + 2 * CH;
constexpr uint32_t OFF_S2 = OFF_S1 + 2 * CH;
constexpr uint32_t OFF_P = OFF_S2 + 2 * CH;
constexpr uint32_t OFF_SC = OFF_P + 4096;
constexpr uint32_t VROW = 272;
constexpr uint32_t OFF_XB = OFF_SC + 8704;
constexpr uint32_t OFF_XA = OFF_XB + 2 * VROW;
constexpr uint32_t OFF_QA = OFF_XA + 2 * VROW;
constexpr uint32_t OFF_QS = OFF_QA + 2 * VROW;
constexpr uint32_t OFF_CC = OFF_QS + 2 * VROW;
constexpr uint32_t OFF_QB = OFF_CC + 4 * VROW;
constexpr uint32_t YHEAD = 288, YROW = 4 * YHEAD + 16;
constexpr uint32_t OFF_Y = OFF_P;
constexpr uint32_t OFF_PAIR = OFF_P + 2 * YROW;
constexpr uint32_t EMPTY = 0xffffffffu;
constexpr uint32_t OFF_LSE = OFF_QB + 256;
constexpr uint32_t OFF_ML = OFF_LSE + 512;
constexpr uint32_t OFF_TAG = OFF_ML + 32;
constexpr uint32_t OFF_NOW = OFF_TAG + 4;
constexpr uint32_t OFF_WIN = OFF_TAG + 8;
constexpr uint32_t OFF_TBOX = OFF_TAG + 12;
constexpr uint32_t OFF_BAR = OFF_TAG + 16;
constexpr int B_EMPTY = RING;
constexpr int B_WQB = 2 * RING;
constexpr int B_WQA = B_WQB + 2;
constexpr int B_WUK = B_WQA + 2;
constexpr int B_WUV = B_WUK + 2;
constexpr int B_CKV = B_WUV + 2;
constexpr int B_WO = B_CKV + 4;
constexpr int B_FREE = B_WO + 8;
constexpr int B_GATH = B_FREE + 1;
constexpr int B_S2 = B_GATH + 1;
constexpr int NBAR = B_S2 + 1;
constexpr uint32_t TS_OFF = OFF_BAR + NBAR * 8;
constexpr uint32_t SMEM_USED = TS_OFF;
constexpr uint32_t SMEM_BYTES = SMEM_USED + 1024;
static_assert(SMEM_BYTES <= 232448, "smem");
static_assert(RING >= WHI && WHI >= WIN && WIN >= 3 && WIN <= 6 && FINE_V % 2 == 0, "windows");

constexpr float LOG2E = 1.4426950408889634f;
constexpr float SCALE = 0.08838834764831845f;
#define SPIN_LOG 22
constexpr uint32_t SPIN_MAX = 1u << SPIN_LOG;

struct Maps { CUtensorMap wqB, wqA, wuk, wuv, woA, woB, ckv, ctxp; };

struct Scratch {
    unsigned cnt[64];
    ulonglong2 e1[2][NCTA][128];
    uint4 qabs[2 * 32 * 64];
    float4 lse[32 * 32];
    uint32_t e4[NCTA][256];
    uint32_t e5[NCTA + 2][128];
    uint4 ctxp[NCTA * 128 * 16];
};
__device__ __align__(256) Scratch g_scratch;

#define TS(k) do {} while (0)

__device__ __forceinline__ void mbar_init(uint32_t b, int c) { asm volatile("mbarrier.init.shared::cta.b64 [%0], %1;" ::"r"(b), "r"(c) : "memory"); }
__device__ __forceinline__ void mbar_expect(uint32_t b, uint32_t bytes) { asm volatile("mbarrier.arrive.expect_tx.shared::cta.b64 _, [%0], %1;" ::"r"(b), "r"(bytes) : "memory"); }
__device__ __forceinline__ void mbar_arrive(uint32_t b) { asm volatile("mbarrier.arrive.shared::cta.b64 _, [%0];" ::"r"(b) : "memory"); }
__device__ __forceinline__ void mbar_wait(uint32_t b, uint32_t ph) {
    uint32_t ok, it = 0;
    do {
        asm volatile("{\n.reg .pred p;\nmbarrier.try_wait.parity.shared::cta.b64 p, [%1], %2;\nselp.u32 %0, 1, 0, p;\n}" : "=r"(ok) : "r"(b), "r"(ph) : "memory");
        if (++it > SPIN_MAX) __trap();
    } while (!ok);
}
__device__ __forceinline__ void mbar_wait_uni(uint32_t b) {
    asm volatile("{\n.reg .pred p, q;\n.reg .u32 n;\nmov.u32 n, 0;\nAGAIN:\nadd.u32 n, n, 1;\nsetp.gt.u32 q, n, %1;\n"
                 "mbarrier.try_wait.parity.shared::cta.b64 p, [%0], 0;\n@q trap;\n@!p bra.uni AGAIN;\n}" ::"r"(b), "n"(SPIN_MAX) : "memory");
}
__device__ __forceinline__ uint32_t mbar_test(uint32_t b, uint32_t ph) {
    uint32_t ok;
    asm volatile("{\n.reg .pred p;\nmbarrier.test_wait.parity.shared::cta.b64 p, [%1], %2;\nselp.u32 %0, 1, 0, p;\n}" : "=r"(ok) : "r"(b), "r"(ph) : "memory");
    return ok;
}
__device__ __forceinline__ void bulk1d(uint32_t dst, const void* src, uint32_t bar, uint64_t pol) {
    asm volatile("cp.async.bulk.shared::cluster.global.mbarrier::complete_tx::bytes.L2::cache_hint [%0], [%1], %2, [%3], %4;"
                 ::"r"(dst), "l"(src), "n"(CH), "r"(bar), "l"(pol) : "memory");
}
__device__ __forceinline__ void bulk1d_n(uint32_t dst, const void* src, uint32_t bytes, uint32_t bar) {
    asm volatile("cp.async.bulk.shared::cluster.global.mbarrier::complete_tx::bytes [%0], [%1], %2, [%3];"
                 ::"r"(dst), "l"(src), "r"(bytes), "r"(bar) : "memory");
}
__device__ __forceinline__ void tma3d(uint32_t dst, const CUtensorMap* map, int c1, int c2, uint32_t bar, uint64_t pol) {
    asm volatile("cp.async.bulk.tensor.3d.shared::cluster.global.mbarrier::complete_tx::bytes.L2::cache_hint [%0], [%1, {%3,%4,%5}], [%2], %6;"
                 ::"r"(dst), "l"(map), "r"(bar), "r"(0), "r"(c1), "r"(c2), "l"(pol) : "memory");
}
__device__ __forceinline__ void bar_sync(int id, int n) { asm volatile("barrier.cta.sync %0, %1;" ::"r"(id), "r"(n) : "memory"); }
__device__ __forceinline__ void bar_arrive(int id, int n) { asm volatile("barrier.cta.arrive %0, %1;" ::"r"(id), "r"(n) : "memory"); }
__device__ __forceinline__ void ldsm4(uint32_t (&r)[4], uint32_t a) {
    asm volatile("ldmatrix.sync.aligned.m8n8.x4.shared.b16 {%0,%1,%2,%3}, [%4];" : "=r"(r[0]), "=r"(r[1]), "=r"(r[2]), "=r"(r[3]) : "r"(a) : "memory");
}
__device__ __forceinline__ void ldsm4t(uint32_t (&r)[4], uint32_t a) {
    asm volatile("ldmatrix.sync.aligned.m8n8.x4.trans.shared.b16 {%0,%1,%2,%3}, [%4];" : "=r"(r[0]), "=r"(r[1]), "=r"(r[2]), "=r"(r[3]) : "r"(a) : "memory");
}
__device__ __forceinline__ void mma(float (&c)[4], const uint32_t (&a)[4], uint32_t b0, uint32_t b1) {
    asm volatile("mma.sync.aligned.m16n8k16.row.col.f32.bf16.bf16.f32 {%0,%1,%2,%3}, {%4,%5,%6,%7}, {%8,%9}, {%0,%1,%2,%3};"
                 : "+f"(c[0]), "+f"(c[1]), "+f"(c[2]), "+f"(c[3]) : "r"(a[0]), "r"(a[1]), "r"(a[2]), "r"(a[3]), "r"(b0), "r"(b1));
}
__device__ __forceinline__ uint32_t lds32(uint32_t a) { uint32_t v; asm volatile("ld.shared.b32 %0, [%1];" : "=r"(v) : "r"(a) : "memory"); return v; }
__device__ __forceinline__ uint32_t ldsv(uint32_t a) { uint32_t v; asm volatile("ld.volatile.shared.b32 %0, [%1];" : "=r"(v) : "r"(a) : "memory"); return v; }
__device__ __forceinline__ void stsv(uint32_t a, uint32_t v) { asm volatile("st.volatile.shared.b32 [%0], %1;" ::"r"(a), "r"(v) : "memory"); }
__device__ __forceinline__ float ldsf(uint32_t a) { float v; asm volatile("ld.shared.f32 %0, [%1];" : "=f"(v) : "r"(a) : "memory"); return v; }
__device__ __forceinline__ uint4 lds128(uint32_t a) { uint4 v; asm volatile("ld.shared.v4.b32 {%0,%1,%2,%3}, [%4];" : "=r"(v.x), "=r"(v.y), "=r"(v.z), "=r"(v.w) : "r"(a) : "memory"); return v; }
__device__ __forceinline__ void sts16(uint32_t a, uint16_t v) { asm volatile("st.shared.b16 [%0], %1;" ::"r"(a), "h"(v) : "memory"); }
__device__ __forceinline__ void sts32(uint32_t a, uint32_t v) { asm volatile("st.shared.b32 [%0], %1;" ::"r"(a), "r"(v) : "memory"); }
__device__ __forceinline__ void stsf2(uint32_t a, float x, float y) { asm volatile("st.shared.v2.f32 [%0], {%1,%2};" ::"r"(a), "f"(x), "f"(y) : "memory"); }
__device__ __forceinline__ void sts128(uint32_t a, uint4 v) { asm volatile("st.shared.v4.b32 [%0], {%1,%2,%3,%4};" ::"r"(a), "r"(v.x), "r"(v.y), "r"(v.z), "r"(v.w) : "memory"); }
__device__ __forceinline__ uint16_t f2bf(float x) { return __bfloat16_as_ushort(__float2bfloat16_rn(x)); }
__device__ __forceinline__ float bfround(float x) { return __bfloat162float(__float2bfloat16_rn(x)); }
__device__ __forceinline__ uint32_t pack2(float lo, float hi) { uint32_t r; asm("cvt.rn.bf16x2.f32 %0, %1, %2;" : "=r"(r) : "f"(hi), "f"(lo)); return r; }
__device__ __forceinline__ float ex2(float x) { float r; asm("ex2.approx.ftz.f32 %0, %1;" : "=f"(r) : "f"(x)); return r; }
__device__ __forceinline__ float lg2(float x) { float r; asm("lg2.approx.ftz.f32 %0, %1;" : "=f"(r) : "f"(x)); return r; }

__device__ __forceinline__ float rcp(float x) { float r; asm("rcp.approx.ftz.f32 %0, %1;" : "=f"(r) : "f"(x)); return r; }

__device__ __forceinline__ uint32_t gtime() { uint32_t t; asm volatile("mov.u32 %0, %globaltimer_lo;" : "=r"(t)::"memory"); return t; }
__device__ __forceinline__ void sleep_ns(uint32_t ns) {
    uint32_t t0, t;
    asm volatile("mov.u32 %0, %clock;" : "=r"(t0));
    do { __nanosleep(200); asm volatile("mov.u32 %0, %clock;" : "=r"(t)); } while (t - t0 < 2 * ns);
}

__device__ __forceinline__ void ll_store2(ulonglong2* p, float a, float b, uint32_t tag) {
    unsigned long long x = ((unsigned long long)tag << 32) | __float_as_uint(a);
    unsigned long long y = ((unsigned long long)tag << 32) | __float_as_uint(b);
    asm volatile("st.relaxed.gpu.global.v2.b64 [%0], {%1,%2};" ::"l"(p), "l"(x), "l"(y) : "memory");
}
__device__ __forceinline__ void ll_ld2(const void* p, unsigned long long& x, unsigned long long& y) {
    asm volatile("ld.relaxed.gpu.global.v2.b64 {%0,%1}, [%2];" : "=l"(x), "=l"(y) : "l"(p) : "memory");
}
__device__ __forceinline__ void ll_gather4(const ulonglong2* p, uint32_t tag, float& r0, float& r1) {
    unsigned long long x[4], y[4]; uint32_t it = 0;
    while (true) {
        bool ok = true;
#pragma unroll
        for (int k = 0; k < 4; k++) ll_ld2(p + k * 128, x[k], y[k]);
#pragma unroll
        for (int k = 0; k < 4; k++) ok = ok && (uint32_t)(x[k] >> 32) == tag && (uint32_t)(y[k] >> 32) == tag;
        if (ok) break;
        if (++it > SPIN_MAX) __trap();
        __nanosleep(BACKOFF);
    }
    r0 = (__uint_as_float((uint32_t)x[0]) + __uint_as_float((uint32_t)x[1])) + (__uint_as_float((uint32_t)x[2]) + __uint_as_float((uint32_t)x[3]));
    r1 = (__uint_as_float((uint32_t)y[0]) + __uint_as_float((uint32_t)y[1])) + (__uint_as_float((uint32_t)y[2]) + __uint_as_float((uint32_t)y[3]));
}
__device__ __forceinline__ void cnt_rendezvous(unsigned* c, uint32_t target, int tsk) {
    TS(tsk);
    asm volatile("red.release.gpu.global.add.u32 [%0], 1;" ::"l"(c) : "memory");
    if (tsk == 18) TS(tsk + 1);
    uint32_t v, it = 0;
    while (true) {
        asm volatile("ld.acquire.gpu.global.u32 %0, [%1];" : "=r"(v) : "l"(c) : "memory");
        if ((int)(v - target) >= 0) break;
        if (++it > SPIN_MAX) __trap();
        __nanosleep(BACKOFF_RV);
    }
    asm volatile("fence.proxy.async.global;" ::: "memory");
}

__device__ __forceinline__ void matvec_loadA(uint32_t (&a)[8][4], uint32_t tile, uint32_t bar, int w, int lane) {
    const int i = lane >> 3, rr = lane & 7, chunk = 2 * w + (i & 1);
    const uint32_t a0 = tile + (chunk >> 3) * 8192 + (rr + 8 * (i >> 1)) * 128 + (((chunk & 7) ^ rr) << 4);
#pragma unroll
    for (int hh = 0; hh < 2; hh++) {
        mbar_wait(bar + hh * 8, 0);
#pragma unroll
        for (int k = 0; k < 4; k++) ldsm4t(a[hh * 4 + k], a0 + hh * CH + k * 2048);
    }
}
__device__ __forceinline__ void matvec_mma(float (&c)[4], const uint32_t (&a)[8][4], uint32_t vec, int nvec, int lane) {
    const uint32_t va = vec + (lane & (nvec - 1)) * VROW + (lane >> 3) * 16;
    float d[4][4];
#pragma unroll
    for (int q = 0; q < 4; q++) {
        uint32_t b[4];
        ldsm4(b, va + q * 64);
        d[q][0] = d[q][1] = d[q][2] = d[q][3] = 0.f;
        mma(d[q], a[2 * q], b[0], b[1]);
        mma(d[q], a[2 * q + 1], b[2], b[3]);
    }
#pragma unroll
    for (int k = 0; k < 4; k++) c[k] = (d[0][k] + d[1][k]) + (d[2][k] + d[3][k]);
}
__device__ __forceinline__ void matvecT(float (&c)[4], uint32_t tile, uint32_t vec, int nvec, uint32_t bar, int w, int lane) {
    uint32_t a[8][4];
    matvec_loadA(a, tile, bar, w, lane);
    matvec_mma(c, a, vec, nvec, lane);
}
template <class T> __device__ __forceinline__ T* pin(T* p) { asm volatile("" : "+l"(p)); return p; }
__device__ __forceinline__ void post(uint32_t* p, float v) {
    asm volatile("red.relaxed.gpu.global.add.u32 [%0], %1;" ::"l"(p), "r"(~__float_as_uint(v)) : "memory");
}
__device__ __forceinline__ void ld4_if(const void* p, uint4& x, bool need) {
    asm volatile("{\n.reg .pred q;\nsetp.ne.u32 q, %5, 0;\n@q ld.relaxed.gpu.global.v4.b32 {%0,%1,%2,%3}, [%4];\n}"
                 : "+r"(x.x), "+r"(x.y), "+r"(x.z), "+r"(x.w) : "l"(p), "r"((uint32_t)need) : "memory");
}
__device__ __forceinline__ void merge_store(const uint4 (&x)[5], uint32_t dst) {
#pragma unroll
    for (int b = 0; b < 2; b++) {
        const float l0 = __uint_as_float(~(b ? x[4].z : x[4].x)), l1 = __uint_as_float(~(b ? x[4].w : x[4].y));
        const float mx = fmaxf(l0, l1), e0 = ex2(l0 - mx), e1 = ex2(l1 - mx), r = rcp(e0 + e1);
        const uint4 u = x[2 * b], v = x[2 * b + 1];
        const uint32_t lo = pack2((e0 * __uint_as_float(~u.x) + e1 * __uint_as_float(~v.x)) * r, (e0 * __uint_as_float(~u.y) + e1 * __uint_as_float(~v.y)) * r);
        const uint32_t hi = pack2((e0 * __uint_as_float(~u.z) + e1 * __uint_as_float(~v.z)) * r, (e0 * __uint_as_float(~u.w) + e1 * __uint_as_float(~v.w)) * r);
        asm volatile("st.shared.v2.b32 [%0], {%1,%2};" ::"r"(dst + b * YROW), "r"(lo), "r"(hi) : "memory");
    }
}

__global__ void __launch_bounds__(NTHREADS, 1)
fused_decode_kernel(const char* __restrict__ wqraw, Scratch* const sc, const __nv_bfloat16* __restrict__ xA, const __nv_bfloat16* __restrict__ xB,
                    const char* __restrict__ Kc, const char* __restrict__ Vc, const __grid_constant__ Maps maps,
                    __nv_bfloat16* __restrict__ out, const uint32_t zero) {
    unsigned* const cnt = sc->cnt;
    asm volatile("{\n.reg .pred p;\nsetp.eq.u32 p, %1, 0;\n@p cp.async.bulk.prefetch.L2.global [%0], %2;\n}"
                 ::"l"(wqraw + (size_t)blockIdx.x * (2 * CH)), "r"(threadIdx.x), "n"(CH) : "memory");
    extern __shared__ char smem_raw[];
    const uint32_t sm = ((uint32_t)__cvta_generic_to_shared(smem_raw) + 1023u) & ~1023u;
    if (threadIdx.x == 64) {
        unsigned epoch;
        asm volatile("atom.relaxed.gpu.global.add.u32 %0, [%1], 1;" : "=r"(epoch) : "l"(cnt) : "memory");
        sts32(sm + OFF_TAG, (epoch >> 7) + 1u);
    }
    const uint32_t bars = sm + OFF_BAR;
    const int cta = blockIdx.x, h = cta >> 2, j = cta & 3;
    uint64_t pol = 0;
    if (threadIdx.x == 0) {
        TS(0);
        asm volatile("createpolicy.fractional.L2::evict_first.b64 %0, 1.0;" : "=l"(pol));
#pragma unroll
        for (int i = 0; i < WIN; i++) mbar_init(bars + (B_WQB + i) * 8, 1);
        asm volatile("fence.mbarrier_init.release.cluster;" ::: "memory");
#pragma unroll
        for (int i = 0; i < WIN; i++) {
            mbar_expect(bars + (B_WQB + i) * 8, CH);
            tma3d(sm + OFF_S0 + i * CH, &maps.wqB + (i >> 1), j * 128 + (i & 1) * 64, h * 2, bars + (B_WQB + i) * 8, pol);
        }
    }
    const int tid = threadIdx.x < 64 ? threadIdx.x + 384 : threadIdx.x - 64, warp = tid >> 5, lane = tid & 31;

    if (warp == 12) {
        const size_t kvoff = ((size_t)(((j >> 1) * 32 + h) * 4096 + (j & 1) * 2048)) * 256;
        const char* kp = Kc + kvoff;
        const char* vp = Vc + kvoff;
        __syncwarp();
        bar_arrive(0, NTHREADS);
        bar_sync(3, 64);
        if (lane == 0) {
            uint32_t pb[WHI];
#pragma unroll
            for (int i = 0; i < WHI; i++) pb[i] = i < WHI - WIN ? (bars + B_WO * 8) | 1u : bars + (B_WQB + i - (WHI - WIN)) * 8;
            auto pace = [&](uint32_t bar, uint32_t par) {
                uint32_t it = 0;
                while (true) {
                    const uint32_t win = ldsv(sm + OFF_WIN);
                    uint32_t busy = 0;
#pragma unroll
                    for (int i = 0; i < WHI; i++) busy += mbar_test(pb[i] & ~1u, pb[i] & 1u) ^ 1u;
                    if (busy < win) break;
                    if (++it > SPIN_MAX) __trap();
                }
#pragma unroll
                for (int i = 0; i + 1 < WHI; i++) pb[i] = pb[i + 1];
                pb[WHI - 1] = bar | par;
            };
            auto side = [&](const CUtensorMap* m, uint32_t dst, int bidx, int c1, int c2) {
                const uint32_t bar = bars + bidx * 8;
                pace(bar, 0);
                mbar_expect(bar, CH);
                tma3d(dst, m, c1, c2, bar, pol);
            };
#pragma unroll 1
            for (int i = WIN; i < 6; i++)
                side(&maps.wqB + (i >> 1), sm + OFF_S0 + i * CH, B_WQB + i, j * 128 + (i & 1) * 64, h * 2);
            TS(1);
            uint32_t slot = 0, use = 0;
            int nuv = 0;
#pragma unroll 1
            for (int n = 0; n < 2 * NTILE; n++) {
                if (n == RING) {
                    mbar_wait(bars + B_FREE * 8, 0);
#pragma unroll 1
                    for (int q = 0; q < 4; q++) side(&maps.ckv, sm + OFF_S0 + q * CH, B_CKV + q, cta * 64 + q * 16, 0);
                }
                if (nuv < 2 && n > RING && (n >= 2 * NTILE - 8 || mbar_test(bars + B_FREE * 8, 1))) {
                    mbar_wait(bars + B_FREE * 8, 1);
                    side(&maps.wuv, sm + OFF_S1 + nuv * CH, B_WUV + nuv, j * 128 + nuv * 64, h * 2);
                    nuv++;
                }
                const uint32_t fb = bars + slot * 8;
                pace(fb, use & 1);
                mbar_wait(fb + B_EMPTY * 8, (use & 1) ^ 1);
                mbar_expect(fb, CH);
                bulk1d(sm + OFF_RING + slot * CH, ((n & 1) ? vp : kp) + (size_t)(n >> 1) * CH, fb, pol);
                if (n >= FINE_V || (n & 1)) {
                    asm volatile("red.relaxed.gpu.global.add.u32 [%0], %1;" ::"l"(cnt + 3), "r"(n >= FINE_V ? 1 : 2) : "memory");
                    stsv(sm + OFF_NOW, n + 1);
                }
                if (++slot == RING) { slot = 0; use++; }
            }
            TS(2);
            mbar_wait(bars + B_FREE * 8, 0);
            uint32_t it = 0;
#pragma unroll 1
            for (int q = 0; q < 8; q++) {
                const uint32_t bar = bars + (B_WO + q) * 8;
                mbar_expect(bar, CH / 2);
                while (true) {
                    const uint32_t t0 = ldsv(sm + OFF_TBOX);
                    if (t0 && gtime() - t0 + 16384u >= 16384u + q * BOX_NS) break;
                    if (++it > SPIN_MAX) __trap();
                }
                tma3d(sm + OFF_S0 + q * (CH / 2), &maps.woA + (cta & 1), (cta >> 4) * 512 + q * 64, (cta >> 1) & 7, bar, pol);
            }
            TS(3);
        }
    } else if (warp == 13) {
        if (lane == 0) {
#pragma unroll
            for (int i = 0; i < NBAR; i++)
                if (i < B_WQB || i >= B_WQB + WIN)
                    mbar_init(bars + i * 8, i == B_FREE ? 8 : (i >= B_EMPTY && i < B_EMPTY + RING) ? 4 : 1);
            asm volatile("fence.mbarrier_init.release.cluster;" ::: "memory");
#pragma unroll
            for (int i = 2; i < 8; i++) asm volatile("prefetch.tensormap [%0];" ::"l"(&maps.wqB + i) : "memory");
            stsv(sm + OFF_NOW, 0); stsv(sm + OFF_WIN, WIN); stsv(sm + OFF_TBOX, 0);
        }
        __syncwarp();
        bar_arrive(3, 64);
        bar_sync(0, NTHREADS);
        if (lane == 0) {
            const uint32_t base = (lds32(sm + OFF_TAG) - 1u) * (NCTA * 2 * NTILE);
            mbar_wait(bars + (B_WUK + 1) * 8, 0);
            uint32_t it = 0, tbox = 0;
            while (true) {
                const uint32_t n = ldsv(sm + OFF_NOW);
                uint32_t v;
                asm volatile("ld.relaxed.gpu.global.u32 %0, [%1];" : "=r"(v) : "l"(cnt + 3) : "memory");
                v -= base;
                if (v >= NCTA * EST_FROM && (v <= NCTA * EST_TO || !tbox)) {
                    const uint32_t est = (gtime() + (NCTA * 2 * NTILE - v) * BOX_NS / 64 + (uint32_t)(BOX_SHIFT + (cta * 37 & 127) * BOX_SPREAD / 128)) | 1u;
                    if (!tbox || (int)(est - tbox) < 0) { tbox = est; stsv(sm + OFF_TBOX, est); }
                }
                if (v >= NCTA * 2 * NTILE - GATE_W) break;
                const int diff = (int)(n * NCTA) - (int)v;
                stsv(sm + OFF_WIN, diff < -THETA ? WHI : WIN - (diff > THETA) - (v >= NCTA * END_V));
                if (++it > SPIN_MAX) __trap();
                __nanosleep(v < NCTA * FINE_V ? BACKOFF3 : BACKOFF2);
            }
            stsv(sm + OFF_WIN, WHI);
            TS(24);
        }
    } else if (warp < 4) {
        const int g = lane >> 2, t = lane & 3, i = lane >> 3, rr = lane & 7;
        bar_sync(0, NTHREADS);
        const uint32_t tag = lds32(sm + OFF_TAG);
        {
            mbar_wait(bars + 8, 0);
            float q0, q1;
            ll_gather4(&sc->e1[0][h * 4][tid], tag, q0, q1);
            sts16(sm + OFF_QB + tid * 2, f2bf((j >> 1) ? q1 : q0));
        }
        bar_sync(1, 128);
        if (tid == 0) TS(4);
        uint32_t qf[8][2];
#pragma unroll
        for (int c = 0; c < 8; c++) {
            const uint32_t a = sm + OFF_QB + (((c + g) & 7) * 8 + 2 * t) * 2;
            qf[c][0] = lds32(a); qf[c][1] = lds32(a + 128);
        }
        float acc[8][4];
#pragma unroll
        for (int c = 0; c < 8; c++) { acc[c][0] = acc[c][1] = acc[c][2] = acc[c][3] = 0.f; }
        float m = -INFINITY, l = 0.f;
        const bool diag = (t == (g >> 1));
        const uint32_t krow = sm + OFF_RING + (warp * 16 + rr + 8 * (i & 1)) * 256 + (i >> 1) * 128;
        const uint32_t vrow = sm + OFF_RING + (warp * 16 + rr + 8 * (i >> 1)) * 256 + (i & 1) * 128;
        uint32_t slot = 0, ph = 0;
        uint32_t* const e5own = pin(&sc->e5[cta][tid]);
        uint32_t a[8][4], b0, b1;
#pragma unroll 1
        for (int tile = 0;; tile++) {
            mbar_wait(bars + slot * 8, ph);
#pragma unroll
            for (int c = 0; c < 8; c++) ldsm4(a[c], krow + slot * CH + (((c + rr) & 7) << 4));
            __syncwarp();
            if (lane == 0) mbar_arrive(bars + (B_EMPTY + slot) * 8 + ((a[0][0] | a[1][0] | a[2][0] | a[3][0] | a[4][0] | a[5][0] | a[6][0] | a[7][0]) & zero));
            if (++slot == RING) { slot = 0; ph ^= 1; }
            float s0[4] = {0.f, 0.f, 0.f, 0.f}, s1[4] = {0.f, 0.f, 0.f, 0.f};
#pragma unroll
            for (int c = 0; c < 8; c += 2) { mma(s0, a[c], qf[c][0], qf[c][1]); mma(s1, a[c + 1], qf[c + 1][0], qf[c + 1][1]); }
            float slo = (g & 1) ? s0[1] + s1[1] : s0[0] + s1[0];
            float shi = (g & 1) ? s0[3] + s1[3] : s0[2] + s1[2];
            slo = diag ? bfround(bfround(slo) * SCALE) : -INFINITY;
            shi = diag ? bfround(bfround(shi) * SCALE) : -INFINITY;
            int key = __float_as_int(fmaxf(slo, shi));
            key ^= (key >> 31) & 0x7fffffff;
            key = __reduce_max_sync(0xffffffffu, key);
            key ^= (key >> 31) & 0x7fffffff;
            const float mn = fmaxf(m, __int_as_float(key));
            const float alpha = ex2((m - mn) * LOG2E);
            m = mn;
            const float plo = ex2((slo - mn) * LOG2E), phi = ex2((shi - mn) * LOG2E);
            l = l * alpha + (plo + phi);
            b0 = (g & 1) ? pack2(0.f, plo) : pack2(plo, 0.f);
            b1 = (g & 1) ? pack2(0.f, phi) : pack2(phi, 0.f);
#pragma unroll
            for (int c = 0; c < 8; c++) { acc[c][0] *= alpha; acc[c][1] *= alpha; acc[c][2] *= alpha; acc[c][3] *= alpha; }
            if (tile == NTILE - 1) break;
            mbar_wait(bars + slot * 8, ph);
#pragma unroll
            for (int c = 0; c < 8; c++) ldsm4t(a[c], vrow + slot * CH + (((c + rr) & 7) << 4));
            __syncwarp();
            if (lane == 0) mbar_arrive(bars + (B_EMPTY + slot) * 8 + ((a[0][0] | a[1][0] | a[2][0] | a[3][0] | a[4][0] | a[5][0] | a[6][0] | a[7][0]) & zero));
            if (++slot == RING) { slot = 0; ph ^= 1; }
#pragma unroll
            for (int c = 0; c < 8; c++) mma(acc[c], a[c], b0, b1);
        }
#pragma unroll
        for (int o = 16; o; o >>= 1) l += __shfl_xor_sync(0xffffffffu, l, o);
        if (lane == 0) stsf2(sm + OFF_ML + warp * 8, m, l);
        mbar_wait(bars + B_S2 * 8, 0);
        bar_sync(1, 128);
        {
            const uint4 ml0 = lds128(sm + OFF_ML), ml1 = lds128(sm + OFF_ML + 16);
            const float m0 = __uint_as_float(ml0.x), m1 = __uint_as_float(ml0.z), m2 = __uint_as_float(ml1.x), m3 = __uint_as_float(ml1.z);
            const float M = fmaxf(fmaxf(m0, m1), fmaxf(m2, m3));
            const float L = (ex2((m0 - M) * LOG2E) * __uint_as_float(ml0.y) + ex2((m1 - M) * LOG2E) * __uint_as_float(ml0.w))
                          + (ex2((m2 - M) * LOG2E) * __uint_as_float(ml1.y) + ex2((m3 - M) * LOG2E) * __uint_as_float(ml1.w));
            const float f = ex2((m - M) * LOG2E) * rcp(L);
            if (tid == 0) post(e5own + (NCTA - cta) * 128 + cta, M * LOG2E + lg2(L));
            mbar_wait(bars + slot * 8, ph);
#pragma unroll
            for (int c = 0; c < 8; c++) ldsm4t(a[c], vrow + slot * CH + (((c + rr) & 7) << 4));
#pragma unroll
            for (int c = 0; c < 8; c++) mma(acc[c], a[c], b0, b1);
            if (tid == 0) TS(5);
            float v[2][8];
#pragma unroll
            for (int c = 0; c < 8; c++) { v[0][c] = acc[c][0] + acc[(c + 7) & 7][1]; v[1][c] = acc[c][2] + acc[(c + 7) & 7][3]; }
#pragma unroll
            for (int c = 0; c < 4; c++) { v[0][c] += __shfl_xor_sync(0xffffffffu, v[0][c + 4], 2); v[1][c] += __shfl_xor_sync(0xffffffffu, v[1][c + 4], 2); }
            const int src = (lane & ~3) | ((lane + 3) & 3);
#pragma unroll
            for (int c = 0; c < 2; c++) { v[0][c] += __shfl_sync(0xffffffffu, v[0][c + 2], src); v[1][c] += __shfl_sync(0xffffffffu, v[1][c + 2], src); }
            const uint32_t wa = sm + OFF_S2 + (warp * 160 + 16 * t + 8 * (t >> 1) + g) * 4;
            sts32(wa, __float_as_uint(v[0][0] * f)); sts32(wa + 32, __float_as_uint(v[0][1] * f));
            sts32(wa + 320, __float_as_uint(v[1][0] * f)); sts32(wa + 352, __float_as_uint(v[1][1] * f));
            bar_sync(1, 128);
            const uint32_t ra = sm + OFF_S2 + (tid + warp * 8) * 4;
            post(e5own, (ldsf(ra) + ldsf(ra + 640)) + (ldsf(ra + 1280) + ldsf(ra + 1920)));
        }
        if (tid == 0) TS(6);
        if (cta & 1) {
            const int c0 = (cta & ~15) + warp * 4;
            const uint32_t* p = e5own + ((c0 - cta) * 128 + lane * 4 - tid);
            const uint32_t* pl = e5own + ((NCTA - cta) * 128 + c0 - tid);
            uint4 x[5];
            bool need[5] = {true, true, true, true, true};
            uint32_t it = 0;
            while (true) {
#pragma unroll
                for (int q = 0; q < 5; q++) ld4_if(q < 4 ? p + q * 128 : pl, x[q], need[q]);
#pragma unroll
                for (int q = 0; q < 5; q++) need[q] = !x[q].x || !x[q].y || !x[q].z || !x[q].w;
                if (!__any_sync(0xffffffffu, need[0] | need[1] | need[2] | need[3] | need[4])) break;
                if (++it > SPIN_MAX) __trap();
            }
            merge_store(x, sm + OFF_Y + warp * YHEAD + lane * 8);
            bar_arrive(4, 256 + 128);
        }
        if (tid == 0) TS(16);
    } else {
        const int st = tid - 128, w = warp - 4;
        const int g = lane >> 2, t = lane & 3, i = lane >> 3, rr = lane & 7;
        if (st < 64) {
            const int which = st >> 5, b = (st >> 4) & 1, c = st & 15;
            const uint4 v = __ldg((const uint4*)((which ? xA : xB) + b * 512 + j * 128) + c);
            sts128(sm + OFF_XB + (which * 2 + b) * VROW + c * 16, v);
        }
        bar_sync(0, NTHREADS);
        const uint32_t tag = lds32(sm + OFF_TAG);
        float c[4];
#pragma unroll 1
        for (int which = 0; which < 2; which++) {
            matvecT(c, sm + OFF_S0 + which * 2 * CH, sm + OFF_XB + which * 2 * VROW, 2, bars + (B_WQB + which * 2) * 8, w, lane);
            if (t == 0) {
                ll_store2(&sc->e1[which][cta][w * 16 + g], c[0], c[1], tag);
                ll_store2(&sc->e1[which][cta][w * 16 + g + 8], c[2], c[3], tag);
            }
        }
        __syncwarp();
        if (lane == 0) mbar_arrive(bars + B_FREE * 8);
        if (st == 0) TS(8);
        if (st < 128) {
            float q0, q1;
            sleep_ns(POLL_DELAY);
            ll_gather4(&sc->e1[1][h * 4][st], tag, q0, q1);
            sts16(sm + OFF_QA + st * 2, f2bf(q0)); sts16(sm + OFF_QA + VROW + st * 2, f2bf(q1));
        }
        bar_sync(2, 256);
        if (st == 0) TS(9);
        {
            const int row = w * 16 + rr + 8 * (i & 1);
            const uint32_t a0 = sm + OFF_S2 + (row >> 6) * CH + (row & 63) * 128;
            const uint32_t va = sm + OFF_QA + g * VROW + t * 4;
            float d[4] = {0.f, 0.f, 0.f, 0.f};
            c[0] = c[1] = c[2] = c[3] = 0.f;
            mbar_wait(bars + (B_WUK + (w >> 2)) * 8, 0);
#pragma unroll
            for (int ks = 0; ks < 8; ks++) {
                const int chunk = 2 * ks + (i >> 1);
                uint32_t a[4];
                ldsm4(a, a0 + (chunk >> 3) * 8192 + (((chunk & 7) ^ rr) << 4));
                const uint32_t b0 = (g < 2) ? lds32(va + ks * 32) : 0u, b1 = (g < 2) ? lds32(va + ks * 32 + 16) : 0u;
                if (ks & 1) mma(d, a, b0, b1); else mma(c, a, b0, b1);
            }
            if (t == 0) {
                const uint32_t qs = sm + OFF_QS + (w * 16 + g) * 2;
                sts16(qs, f2bf(c[0] + d[0])); sts16(qs + VROW, f2bf(c[1] + d[1]));
                sts16(qs + 16, f2bf(c[2] + d[2])); sts16(qs + VROW + 16, f2bf(c[3] + d[3]));
            }
            bar_sync(2, 256);
            if (w == 0) {
                const int b = lane >> 4, cc = lane & 15;
                sc->qabs[(b * 32 + h) * 64 + ((j * 16 + cc) ^ (h & 7))] = lds128(sm + OFF_QS + b * VROW + cc * 16);
                __syncwarp();
                if (lane == 0) {
                    cnt_rendezvous(cnt + 1, tag * 128u, 18);
                    TS(10);
                    mbar_expect(bars + B_GATH * 8, 2 * CH);
                    bulk1d_n(sm + OFF_S2, sc->qabs + (cta >> 6) * 2048, 2 * CH, bars + B_GATH * 8);
                }
                __syncwarp();
            }
        }
        mbar_wait(bars + B_GATH * 8, 0);
        if (st == 0) TS(11);
        {
            const int mt = w & 1, kg = w >> 1;
            const uint32_t qa = sm + OFF_S2 + (mt * 16 + rr + 8 * (i & 1)) * 1024;
            const uint32_t ka = sm + OFF_S0 + kg * CH + (rr + 8 * (i >> 1)) * 128;
            float s0[4] = {0.f, 0.f, 0.f, 0.f}, s1[4] = {0.f, 0.f, 0.f, 0.f};
            mbar_wait(bars + (B_CKV + kg) * 8, 0);
#pragma unroll 2
            for (int gq = 0; gq < 8; gq++) {
#pragma unroll
                for (int k4 = 0; k4 < 4; k4++) {
                    uint32_t a[4], b[4];
                    ldsm4(a, qa + gq * 128 + (((2 * k4 + (i >> 1)) ^ rr) << 4));
                    ldsm4(b, ka + gq * 2048 + (((2 * k4 + (i & 1)) ^ rr) << 4));
                    mma(s0, a, b[0], b[1]);
                    mma(s1, a, b[2], b[3]);
                }
            }
            const uint32_t sa = sm + OFF_SC + ((mt * 16 + g) * 68 + kg * 16 + 2 * t) * 4;
            stsf2(sa, s0[0], s0[1]); stsf2(sa + 32, s1[0], s1[1]);
            stsf2(sa + 8 * 68 * 4, s0[2], s0[3]); stsf2(sa + 8 * 68 * 4 + 32, s1[2], s1[3]);
        }
        bar_sync(2, 256);
        {
            const int head = w * 4 + i;
            const uint32_t sa = sm + OFF_SC + (head * 68 + rr * 8) * 4;
            const uint4 u0 = lds128(sa), u1 = lds128(sa + 16);
            float s[8] = {__uint_as_float(u0.x), __uint_as_float(u0.y), __uint_as_float(u0.z), __uint_as_float(u0.w),
                          __uint_as_float(u1.x), __uint_as_float(u1.y), __uint_as_float(u1.z), __uint_as_float(u1.w)};
            float mx = s[0];
#pragma unroll
            for (int k = 1; k < 8; k++) mx = fmaxf(mx, s[k]);
#pragma unroll
            for (int o = 1; o < 8; o <<= 1) mx = fmaxf(mx, __shfl_xor_sync(0xffffffffu, mx, o));
            float sum = 0.f;
#pragma unroll
            for (int k = 0; k < 8; k++) { s[k] = ex2((s[k] - mx) * (SCALE * LOG2E)); sum += s[k]; }
#pragma unroll
            for (int o = 1; o < 8; o <<= 1) sum += __shfl_xor_sync(0xffffffffu, sum, o);
            const float inv = __fdividef(1.f, sum);
            uint4 p;
            p.x = pack2(s[0] * inv, s[1] * inv); p.y = pack2(s[2] * inv, s[3] * inv);
            p.z = pack2(s[4] * inv, s[5] * inv); p.w = pack2(s[6] * inv, s[7] * inv);
            sts128(sm + OFF_P + head * 128 + ((rr ^ (head & 7)) << 4), p);
            if (rr == 0) ((float*)sc->lse)[head * 128 + cta] = mx * (SCALE * LOG2E) + lg2(sum);
        }
        bar_sync(2, 256);
        {
            float o[2][8][4];
#pragma unroll
            for (int mt = 0; mt < 2; mt++)
#pragma unroll
                for (int n = 0; n < 8; n++) { o[mt][n][0] = o[mt][n][1] = o[mt][n][2] = o[mt][n][3] = 0.f; }
            const uint32_t pa = sm + OFF_P + (rr + 8 * (i & 1)) * 128;
            const uint32_t va = sm + OFF_S0 + w * 2048 + (rr + 8 * (i & 1)) * 128;
#pragma unroll 1
            for (int kq = 0; kq < 4; kq++) {
                uint32_t a0[4], a1[4];
                ldsm4(a0, pa + (((2 * kq + (i >> 1)) ^ rr) << 4));
                ldsm4(a1, pa + 2048 + (((2 * kq + (i >> 1)) ^ rr) << 4));
#pragma unroll
                for (int n = 0; n < 8; n += 2) {
                    uint32_t b[4];
                    ldsm4t(b, va + kq * CH + (((n + (i >> 1)) ^ rr) << 4));
                    mma(o[0][n], a0, b[0], b[1]); mma(o[1][n], a1, b[0], b[1]);
                    mma(o[0][n + 1], a0, b[2], b[3]); mma(o[1][n + 1], a1, b[2], b[3]);
                }
            }
#pragma unroll
            for (int mt = 0; mt < 2; mt++)
#pragma unroll
                for (int hf = 0; hf < 2; hf++) {
                    const uint32_t dst = sm + OFF_S2 + (mt * 16 + hf * 8 + g) * 1024 + w * 128 + t * 16;
#pragma unroll
                    for (int nb = 0; nb < 2; nb++) {
                        uint4 v;
                        v.x = pack2(o[mt][nb * 4 + 0][hf * 2], o[mt][nb * 4 + 0][hf * 2 + 1]);
                        v.y = pack2(o[mt][nb * 4 + 1][hf * 2], o[mt][nb * 4 + 1][hf * 2 + 1]);
                        v.z = pack2(o[mt][nb * 4 + 2][hf * 2], o[mt][nb * 4 + 2][hf * 2 + 1]);
                        v.w = pack2(o[mt][nb * 4 + 3][hf * 2], o[mt][nb * 4 + 3][hf * 2 + 1]);
                        sts128(dst + nb * 64, v);
                    }
                }
            asm volatile("fence.proxy.async.shared::cta;" ::: "memory");
            __syncwarp();
            if (lane == 0) mbar_arrive(bars + B_FREE * 8);
            sc->e4[cta][st] = 0u;
            if (st < 128) sc->e5[cta][st] = 0u;
            else if (cta == 0) sc->e5[NCTA][st - 128] = 0u;
            if (st >= 248) ((uint32_t*)out)[cta * 8 + st - 248] = 0u;
        }
        bar_sync(2, 256);
        if (st == 0) {
            TS(12);
#pragma unroll 1
            for (int k = 0; k < ST_SPLIT; k++) {
                asm volatile("cp.async.bulk.tensor.3d.global.shared::cta.bulk_group [%0, {%2,%3,%4}], [%1];"
                             ::"l"(&maps.ctxp), "r"(sm + OFF_S2 + k * (2 * CH / ST_SPLIT)), "r"(0), "r"(cta), "r"(k * (128 / ST_SPLIT)) : "memory");
                if (k + 1 < ST_SPLIT) __nanosleep(ST_GAP);
            }
            asm volatile("cp.async.bulk.commit_group;" ::: "memory");
            asm volatile("cp.async.bulk.wait_group 0;" ::: "memory");
            cnt_rendezvous(cnt + 2, tag * 128u, 20);
            TS(13);
            mbar_expect(bars + B_GATH * 8, 2 * CH + 512);
            bulk1d_n(sm + OFF_LSE, sc->lse + h * 32, 512, bars + B_GATH * 8);
#pragma unroll 1
            for (int k = 0; k < ST_SPLIT; k++) {
                bulk1d_n(sm + OFF_S2 + k * (2 * CH / ST_SPLIT), sc->ctxp + cta * 2048 + k * (2048 / ST_SPLIT), 2 * CH / ST_SPLIT, bars + B_GATH * 8);
                __nanosleep(LD_GAP);
            }
        }
        __syncwarp();
        {
            mbar_wait(bars + B_GATH * 8, 1);
            if (st == 0) TS(22);
            uint4 v[8];
#pragma unroll
            for (int k = 0; k < 8; k++) v[k] = lds128(sm + OFF_S2 + (k * 256 + st) * 16);
            float ls[4];
#pragma unroll
            for (int k = 0; k < 4; k++) ls[k] = ldsf(sm + OFF_LSE + (k * 32 + lane) * 4);
            float m0 = fmaxf(ls[0], ls[1]), m1 = fmaxf(ls[2], ls[3]);
#pragma unroll
            for (int o = 16; o; o >>= 1) { m0 = fmaxf(m0, __shfl_xor_sync(0xffffffffu, m0, o)); m1 = fmaxf(m1, __shfl_xor_sync(0xffffffffu, m1, o)); }
            ls[0] = ex2(ls[0] - m0); ls[1] = ex2(ls[1] - m0); ls[2] = ex2(ls[2] - m1); ls[3] = ex2(ls[3] - m1);
            float z0 = ls[0] + ls[1], z1 = ls[2] + ls[3];
#pragma unroll
            for (int o = 16; o; o >>= 1) { z0 += __shfl_xor_sync(0xffffffffu, z0, o); z1 += __shfl_xor_sync(0xffffffffu, z1, o); }
            z0 = __fdividef(1.f, z0); z1 = __fdividef(1.f, z1);
            ls[0] *= z0; ls[1] *= z0; ls[2] *= z1; ls[3] *= z1;
            float a[2][8];
#pragma unroll
            for (int e = 0; e < 8; e++) a[0][e] = a[1][e] = 0.f;
            const int rg = st >> 4;
#pragma unroll
            for (int k = 0; k < 8; k++) {
                const float wt = __shfl_sync(0xffffffffu, ls[k >> 1], rg + 16 * (k & 1));
                const uint32_t u[4] = {v[k].x, v[k].y, v[k].z, v[k].w};
#pragma unroll
                for (int e = 0; e < 4; e++) {
                    a[k >> 2][2 * e] += wt * __uint_as_float(u[e] << 16);
                    a[k >> 2][2 * e + 1] += wt * __uint_as_float(u[e] & 0xffff0000u);
                }
            }
            const int b = lane >> 4, u16 = lane & 15;
            const uint32_t ra = sm + OFF_SC + (w * 256 + b * 128 + (u16 >> 3) * 64 + ((u16 >> 2) & 1) * 32 + (u16 & 3) * 2) * 4;
#pragma unroll
            for (int e = 0; e < 8; e += 2) {
                const float k0 = b ? a[1][e] : a[0][e], k1 = b ? a[1][e + 1] : a[0][e + 1];
                const float s0 = b ? a[0][e] : a[1][e], s1 = b ? a[0][e + 1] : a[1][e + 1];
                stsf2(ra + (e >> 1) * 32, k0 + __shfl_xor_sync(0xffffffffu, s0, 16), k1 + __shfl_xor_sync(0xffffffffu, s1, 16));
            }
            bar_sync(2, 256);
            if (st == 0) mbar_arrive(bars + B_S2 * 8);
            float s = 0.f;
#pragma unroll
            for (int k = 0; k < 8; k++) s += ldsf(sm + OFF_SC + (k * 256 + st) * 4);
            const float hi = bfround(s);
            const uint32_t ca = sm + OFF_CC + (st >> 7) * VROW + (st & 127) * 2;
            sts16(ca, f2bf(hi)); sts16(ca + 2 * VROW, f2bf(s - hi));
            bar_sync(2, 256);
        }
        matvecT(c, sm + OFF_S1, sm + OFF_CC, 4, bars + B_WUV * 8, w, lane);
#pragma unroll
        for (int k = 0; k < 4; k++) c[k] += __shfl_xor_sync(0xffffffffu, c[k], 1);
        post(&sc->e4[cta][(t & 1) * 128 + w * 16 + (t >> 1) * 8 + g], t == 0 ? c[0] : t == 1 ? c[1] : t == 2 ? c[2] : c[3]);
        __syncwarp();
        if (lane == 0) mbar_arrive(bars + B_FREE * 8);
        if (st == 0) TS(23);
        if (st < 128) sts32(sm + OFF_PAIR + st * 4, EMPTY);
        if (!(cta & 1)) {
            const uint32_t* p = &sc->e4[(cta & ~15) + (w >> 1) * 4][(w & 1) * 128 + lane * 4];
            uint4 x[4];
            bool need[4] = {true, true, true, true};
            uint32_t it = 0;
            sleep_ns(POLL_DELAY2);
            while (true) {
#pragma unroll
                for (int q = 0; q < 4; q++) ld4_if(p + q * 256, x[q], need[q]);
#pragma unroll
                for (int q = 0; q < 4; q++) need[q] = !x[q].x || !x[q].y || !x[q].z || !x[q].w;
                if (!__any_sync(0xffffffffu, need[0] | need[1] | need[2] | need[3])) break;
                if (++it > SPIN_MAX) __trap();
                __nanosleep(BACKOFF);
            }
            auto sum4 = [](uint32_t a, uint32_t b, uint32_t c, uint32_t d) {
                return (__uint_as_float(~a) + __uint_as_float(~b)) + (__uint_as_float(~c) + __uint_as_float(~d));
            };
            asm volatile("st.shared.v2.b32 [%0], {%1,%2};" ::"r"(sm + OFF_Y + (w & 1) * YROW + (w >> 1) * YHEAD + lane * 8),
                         "r"(pack2(sum4(x[0].x, x[1].x, x[2].x, x[3].x), sum4(x[0].y, x[1].y, x[2].y, x[3].y))),
                         "r"(pack2(sum4(x[0].z, x[1].z, x[2].z, x[3].z), sum4(x[0].w, x[1].w, x[2].w, x[3].w))) : "memory");
        }
        if (st == 0) TS(14);
        bar_sync(2, 256);
        {
            const int hf = w >> 2, cg = w & 3;
            const uint32_t a0 = sm + OFF_S0 + hf * 8192 + (rr + 8 * (i >> 1)) * 128 + (((2 * cg + (i & 1)) ^ rr) << 4);
            const uint32_t va = sm + OFF_Y + (lane >> 1 & 1) * YROW + (lane & 1) * YHEAD + hf * 128 + i * 16;
            const uint32_t wb = bars + (B_WO + hf) * 8;
            const uint32_t pa = sm + OFF_PAIR + (cg * 32 + lane) * 4;
            const int col = (t & 1) * 1024 + (cta & 1) * 512 + (cta >> 1 & 7) * 64 + cg * 16 + (t >> 1) * 8 + g;
            __nv_bfloat16* const outp = pin(out + (col & ~1));
            const bool up = t >= 2, odd = g & 1;
            uint32_t a[4][4][4], b[4][4];
            float d[2][4][4];
#pragma unroll
            for (int k = 0; k < 8; k++) d[k >> 2][k & 3][0] = d[k >> 2][k & 3][1] = d[k >> 2][k & 3][2] = d[k >> 2][k & 3][3] = 0.f;
            auto load_w = [&](int hd) {
                mbar_wait(wb + hd * 16, 0);
#pragma unroll
                for (int k = 0; k < 4; k++) ldsm4t(a[hd][k], a0 + hd * CH + k * 2048);
            };
            auto load_y = [&]() {
#pragma unroll
                for (int q = 0; q < 4; q++) ldsm4(b[q], va + (q >> 1) * 2 * YHEAD + (q & 1) * 64);
            };
            auto head = [&](int hd) {
#pragma unroll
                for (int k = 0; k < 4; k++) mma(d[hd & 1][k], a[hd][k], b[(hd & 2) + (k >> 1)][(k & 1) * 2], b[(hd & 2) + (k >> 1)][(k & 1) * 2 + 1]);
            };
            if (cta & 1) {
                load_w(0); load_w(1);
                bar_sync(4, 256 + 128);
                load_y();
                head(0); head(1);
            } else {
                load_y();
                load_w(0); head(0);
                load_w(1); head(1);
            }
            if (st == 0) TS(25);
            load_w(2); head(2);
            float z = up ? (d[0][0][2] + d[0][1][2]) + (d[0][2][2] + d[0][3][2]) : (d[0][0][0] + d[0][1][0]) + (d[0][2][0] + d[0][3][0]);
            mbar_wait_uni(wb + 48);
            if (st == 0) TS(26);
            uint32_t other = ldsv(pa);
#pragma unroll
            for (int k = 0; k < 4; k++) ldsm4t(a[3][k], a0 + 3 * CH + k * 2048);
            head(3);
            z += other != EMPTY ? __uint_as_float(other) : 0.f;
            float z1 = z, z3 = z;
#pragma unroll
            for (int k = 0; k < 3; k++) { z1 += d[1][k][1]; z3 += d[1][k][3]; }
            z = up ? z3 + d[1][3][3] : z1 + d[1][3][1];
            if (st == 0) TS(17);
            asm volatile("{\n.reg .pred p;\nsetp.eq.u32 p, %2, %3;\n@p bra FIRST;\nred.relaxed.gpu.global.add.noftz.bf16x2 [%0], %1;\nexit;\nFIRST:\n}"
                         ::"l"(outp), "r"(odd ? pack2(0.f, z) : pack2(z, 0.f)), "r"(other), "n"(EMPTY) : "memory");
            asm volatile("atom.shared.exch.b32 %0, [%1], %2;" : "=r"(other) : "r"(pa), "r"(__float_as_uint(z)) : "memory");
            z += __uint_as_float(other);
            asm volatile("{\n.reg .pred p;\nsetp.eq.u32 p, %2, %3;\n@p exit;\nred.relaxed.gpu.global.add.noftz.bf16x2 [%0], %1;\n}"
                         ::"l"(outp), "r"(odd ? pack2(0.f, z) : pack2(z, 0.f)), "r"(other), "n"(EMPTY) : "memory");
        }
    }
}

typedef CUresult (*EncodeFn)(CUtensorMap*, CUtensorMapDataType, cuuint32_t, void*, const cuuint64_t*, const cuuint64_t*,
                             const cuuint32_t*, const cuuint32_t*, CUtensorMapInterleave, CUtensorMapSwizzle,
                             CUtensorMapL2promotion, CUtensorMapFloatOOBfill);

void make_map(EncodeFn enc, CUtensorMap* m, void* p, unsigned rows, unsigned cols, unsigned br, unsigned bg) {
    cuuint64_t gd[3] = {64, rows, cols / 64};
    cuuint64_t gs[2] = {(cuuint64_t)cols * 2, 128};
    cuuint32_t bx[3] = {64, br, bg};
    cuuint32_t es[3] = {1, 1, 1};
    enc(m, CU_TENSOR_MAP_DATA_TYPE_BFLOAT16, 3, p, gd, gs, bx, es, CU_TENSOR_MAP_INTERLEAVE_NONE,
        CU_TENSOR_MAP_SWIZZLE_128B, CU_TENSOR_MAP_L2_PROMOTION_L2_128B, CU_TENSOR_MAP_FLOAT_OOB_FILL_NONE);
}

}

extern "C" void kernel_launch(void* const* d_in, const int* in_sizes, int n_in, void* d_out, int out_size) {
    static EncodeFn enc = nullptr;
    if (!enc) {
        void* fn = nullptr;
        cudaDriverEntryPointQueryResult qr;
        cudaGetDriverEntryPoint("cuTensorMapEncodeTiled", &fn, cudaEnableDefault, &qr);
        enc = (EncodeFn)fn;
        cudaFuncSetAttribute(fused_decode_kernel, cudaFuncAttributeMaxDynamicSharedMemorySize, SMEM_BYTES);
    }
    Scratch* sc = nullptr;
    cudaGetSymbolAddress((void**)&sc, g_scratch);
    Maps maps;
    make_map(enc, &maps.wqB, d_in[9], 512, 4096, 64, 2);
    make_map(enc, &maps.wqA, d_in[2], 512, 4096, 64, 2);
    make_map(enc, &maps.wuk, d_in[3], 512, 4096, 64, 2);
    make_map(enc, &maps.wuv, d_in[4], 512, 4096, 64, 2);
    make_map(enc, &maps.woA, d_in[5], 4096, 512, 64, 1);
    make_map(enc, &maps.woB, d_in[10], 4096, 512, 64, 1);
    make_map(enc, &maps.ckv, d_in[1], 8192, 512, 16, 8);
    {
        void* p = sc->ctxp;
        cuuint64_t gd[3] = {128, 128, 128};
        cuuint64_t gs[2] = {256, 32768};
        cuuint32_t bx[3] = {128, 1, 128 / ST_SPLIT};
        cuuint32_t es[3] = {1, 1, 1};
        enc(&maps.ctxp, CU_TENSOR_MAP_DATA_TYPE_BFLOAT16, 3, p, gd, gs, bx, es, CU_TENSOR_MAP_INTERLEAVE_NONE,
            CU_TENSOR_MAP_SWIZZLE_NONE, CU_TENSOR_MAP_L2_PROMOTION_NONE, CU_TENSOR_MAP_FLOAT_OOB_FILL_NONE);
    }
    fused_decode_kernel<<<NCTA, NTHREADS, SMEM_BYTES>>>((const char*)d_in[9], sc, (const __nv_bfloat16*)d_in[0], (const __nv_bfloat16*)d_in[6],
                                                         (const char*)d_in[7], (const char*)d_in[8], maps, (__nv_bfloat16*)d_out, 0u);
}
```

```cpp
#include <cuda_runtime.h>
#include <cuda.h>
#include <cuda_bf16.h>
#include <stdint.h>

#define RING 7
#define WIN 4
#define WHI 5
#define THETA 64
#define END_V 40
#define GATE_W 64
#define BOX_NS 319
#define BOX_SHIFT -25
#define EST_FROM 57
#define EST_TO 62
#define POLL_DELAY 3000
#define POLL_DELAY2 2500
#define ST_SPLIT 8
#define ST_GAP 500
#define LD_GAP 300
#define BACKOFF 200
#define BACKOFF_RV 800
#define FINE_V 52
#define BACKOFF2 100
#define BACKOFF3 300

namespace {

constexpr int NCTA = 128;
constexpr int NTHREADS = 448;
constexpr uint32_t CH = 16384;
constexpr int NTILE = 32;

constexpr uint32_t OFF_RING = 0;
constexpr uint32_t OFF_S0 = RING * CH;
constexpr uint32_t OFF_S1 = OFF_S0 + 2 * CH;
constexpr uint32_t OFF_S2 = OFF_S1 + 2 * CH;
constexpr uint32_t OFF_P = OFF_S2 + 2 * CH;
constexpr uint32_t OFF_SC = OFF_P + 4096;
constexpr uint32_t VROW = 272;
constexpr uint32_t OFF_XB = OFF_SC + 8704;
constexpr uint32_t OFF_XA = OFF_XB + 2 * VROW;
constexpr uint32_t OFF_QA = OFF_XA + 2 * VROW;
constexpr uint32_t OFF_QS = OFF_QA + 2 * VROW;
constexpr uint32_t OFF_CC = OFF_QS + 2 * VROW;
constexpr uint32_t OFF_QB = OFF_CC + 4 * VROW;
constexpr uint32_t YHEAD = 288, YROW = 4 * YHEAD + 16;
constexpr uint32_t OFF_Y = OFF_P;
constexpr uint32_t OFF_PAIR = OFF_P + 2 * YROW;
constexpr uint32_t EMPTY = 0xffffffffu;
constexpr uint32_t OFF_LSE = OFF_QB + 256;
constexpr uint32_t OFF_ML = OFF_LSE + 512;
constexpr uint32_t OFF_TAG = OFF_ML + 32;
constexpr uint32_t OFF_NOW = OFF_TAG + 4;
constexpr uint32_t OFF_WIN = OFF_TAG + 8;
constexpr uint32_t OFF_TBOX = OFF_TAG + 12;
constexpr uint32_t OFF_BAR = OFF_TAG + 16;
constexpr int B_EMPTY = RING;
constexpr int B_WQB = 2 * RING;
constexpr int B_WQA = B_WQB + 2;
constexpr int B_WUK = B_WQA + 2;
constexpr int B_WUV = B_WUK + 2;
constexpr int B_CKV = B_WUV + 2;
constexpr int B_WO = B_CKV + 4;
constexpr int B_FREE = B_WO + 8;
constexpr int B_GATH = B_FREE + 1;
constexpr int B_S2 = B_GATH + 1;
constexpr int NBAR = B_S2 + 1;
constexpr uint32_t TS_OFF = OFF_BAR + NBAR * 8;
constexpr uint32_t SMEM_USED = TS_OFF;
constexpr uint32_t SMEM_BYTES = SMEM_USED + 1024;
static_assert(SMEM_BYTES <= 232448, "smem");
static_assert(RING >= WHI && WHI >= WIN && WIN >= 3 && WIN <= 6 && FINE_V % 2 == 0, "windows");

constexpr float LOG2E = 1.4426950408889634f;
constexpr float SCALE = 0.08838834764831845f;
#define SPIN_LOG 22
constexpr uint32_t SPIN_MAX = 1u << SPIN_LOG;

struct Maps { CUtensorMap wqB, wqA, wuk, wuv, woA, woB, ckv, ctxp; };

struct Scratch {
    unsigned cnt[64];
    ulonglong2 e1[2][NCTA][128];
    uint4 qabs[2 * 32 * 64];
    float4 lse[32 * 32];
    uint32_t e4[NCTA][256];
    uint32_t e5[NCTA + 2][128];
    uint4 ctxp[NCTA * 128 * 16];
};
__device__ __align__(256) Scratch g_scratch;

#define TS(k) do {} while (0)

__device__ __forceinline__ void mbar_init(uint32_t b, int c) { asm volatile("mbarrier.init.shared::cta.b64 [%0], %1;" ::"r"(b), "r"(c) : "memory"); }
__device__ __forceinline__ void mbar_expect(uint32_t b, uint32_t bytes) { asm volatile("mbarrier.arrive.expect_tx.shared::cta.b64 _, [%0], %1;" ::"r"(b), "r"(bytes) : "memory"); }
__device__ __forceinline__ void mbar_arrive(uint32_t b) { asm volatile("mbarrier.arrive.shared::cta.b64 _, [%0];" ::"r"(b) : "memory"); }
__device__ __forceinline__ void mbar_wait(uint32_t b, uint32_t ph) {
    uint32_t ok, it = 0;
    do {
        asm volatile("{\n.reg .pred p;\nmbarrier.try_wait.parity.shared::cta.b64 p, [%1], %2;\nselp.u32 %0, 1, 0, p;\n}" : "=r"(ok) : "r"(b), "r"(ph) : "memory");
        if (++it > SPIN_MAX) __trap();
    } while (!ok);
}
__device__ __forceinline__ void mbar_wait_uni(uint32_t b) {
    asm volatile("{\n.reg .pred p, q;\n.reg .u32 n;\nmov.u32 n, 0;\nAGAIN:\nadd.u32 n, n, 1;\nsetp.gt.u32 q, n, %1;\n"
                 "mbarrier.try_wait.parity.shared::cta.b64 p, [%0], 0;\n@q trap;\n@!p bra.uni AGAIN;\n}" ::"r"(b), "n"(SPIN_MAX) : "memory");
}
__device__ __forceinline__ uint32_t mbar_test(uint32_t b, uint32_t ph) {
    uint32_t ok;
    asm volatile("{\n.reg .pred p;\nmbarrier.test_wait.parity.shared::cta.b64 p, [%1], %2;\nselp.u32 %0, 1, 0, p;\n}" : "=r"(ok) : "r"(b), "r"(ph) : "memory");
    return ok;
}
__device__ __forceinline__ void bulk1d(uint32_t dst, const void* src, uint32_t bar, uint64_t pol) {
    asm volatile("cp.async.bulk.shared::cluster.global.mbarrier::complete_tx::bytes.L2::cache_hint [%0], [%1], %2, [%3], %4;"
                 ::"r"(dst), "l"(src), "n"(CH), "r"(bar), "l"(pol) : "memory");
}
__device__ __forceinline__ void bulk1d_n(uint32_t dst, const void* src, uint32_t bytes, uint32_t bar) {
    asm volatile("cp.async.bulk.shared::cluster.global.mbarrier::complete_tx::bytes [%0], [%1], %2, [%3];"
                 ::"r"(dst), "l"(src), "r"(bytes), "r"(bar) : "memory");
}
__device__ __forceinline__ void tma3d(uint32_t dst, const CUtensorMap* map, int c1, int c2, uint32_t bar, uint64_t pol) {
    asm volatile("cp.async.bulk.tensor.3d.shared::cluster.global.mbarrier::complete_tx::bytes.L2::cache_hint [%0], [%1, {%3,%4,%5}], [%2], %6;"
                 ::"r"(dst), "l"(map), "r"(bar), "r"(0), "r"(c1), "r"(c2), "l"(pol) : "memory");
}
__device__ __forceinline__ void bar_sync(int id, int n) { asm volatile("barrier.cta.sync %0, %1;" ::"r"(id), "r"(n) : "memory"); }
__device__ __forceinline__ void bar_arrive(int id, int n) { asm volatile("barrier.cta.arrive %0, %1;" ::"r"(id), "r"(n) : "memory"); }
__device__ __forceinline__ void ldsm4(uint32_t (&r)[4], uint32_t a) {
    asm volatile("ldmatrix.sync.aligned.m8n8.x4.shared.b16 {%0,%1,%2,%3}, [%4];" : "=r"(r[0]), "=r"(r[1]), "=r"(r[2]), "=r"(r[3]) : "r"(a) : "memory");
}
__device__ __forceinline__ void ldsm4t(uint32_t (&r)[4], uint32_t a) {
    asm volatile("ldmatrix.sync.aligned.m8n8.x4.trans.shared.b16 {%0,%1,%2,%3}, [%4];" : "=r"(r[0]), "=r"(r[1]), "=r"(r[2]), "=r"(r[3]) : "r"(a) : "memory");
}
__device__ __forceinline__ void mma(float (&c)[4], const uint32_t (&a)[4], uint32_t b0, uint32_t b1) {
    asm volatile("mma.sync.aligned.m16n8k16.row.col.f32.bf16.bf16.f32 {%0,%1,%2,%3}, {%4,%5,%6,%7}, {%8,%9}, {%0,%1,%2,%3};"
                 : "+f"(c[0]), "+f"(c[1]), "+f"(c[2]), "+f"(c[3]) : "r"(a[0]), "r"(a[1]), "r"(a[2]), "r"(a[3]), "r"(b0), "r"(b1));
}
__device__ __forceinline__ uint32_t lds32(uint32_t a) { uint32_t v; asm volatile("ld.shared.b32 %0, [%1];" : "=r"(v) : "r"(a) : "memory"); return v; }
__device__ __forceinline__ uint32_t ldsv(uint32_t a) { uint32_t v; asm volatile("ld.volatile.shared.b32 %0, [%1];" : "=r"(v) : "r"(a) : "memory"); return v; }
__device__ __forceinline__ void stsv(uint32_t a, uint32_t v) { asm volatile("st.volatile.shared.b32 [%0], %1;" ::"r"(a), "r"(v) : "memory"); }
__device__ __forceinline__ float ldsf(uint32_t a) { float v; asm volatile("ld.shared.f32 %0, [%1];" : "=f"(v) : "r"(a) : "memory"); return v; }
__device__ __forceinline__ uint4 lds128(uint32_t a) { uint4 v; asm volatile("ld.shared.v4.b32 {%0,%1,%2,%3}, [%4];" : "=r"(v.x), "=r"(v.y), "=r"(v.z), "=r"(v.w) : "r"(a) : "memory"); return v; }
__device__ __forceinline__ void sts16(uint32_t a, uint16_t v) { asm volatile("st.shared.b16 [%0], %1;" ::"r"(a), "h"(v) : "memory"); }
__device__ __forceinline__ void sts32(uint32_t a, uint32_t v) { asm volatile("st.shared.b32 [%0], %1;" ::"r"(a), "r"(v) : "memory"); }
__device__ __forceinline__ void stsf2(uint32_t a, float x, float y) { asm volatile("st.shared.v2.f32 [%0], {%1,%2};" ::"r"(a), "f"(x), "f"(y) : "memory"); }
__device__ __forceinline__ void sts128(uint32_t a, uint4 v) { asm volatile("st.shared.v4.b32 [%0], {%1,%2,%3,%4};" ::"r"(a), "r"(v.x), "r"(v.y), "r"(v.z), "r"(v.w) : "memory"); }
__device__ __forceinline__ uint16_t f2bf(float x) { return __bfloat16_as_ushort(__float2bfloat16_rn(x)); }
__device__ __forceinline__ float bfround(float x) { return __bfloat162float(__float2bfloat16_rn(x)); }
__device__ __forceinline__ uint32_t pack2(float lo, float hi) { uint32_t r; asm("cvt.rn.bf16x2.f32 %0, %1, %2;" : "=r"(r) : "f"(hi), "f"(lo)); return r; }
__device__ __forceinline__ float ex2(float x) { float r; asm("ex2.approx.ftz.f32 %0, %1;" : "=f"(r) : "f"(x)); return r; }
__device__ __forceinline__ float lg2(float x) { float r; asm("lg2.approx.ftz.f32 %0, %1;" : "=f"(r) : "f"(x)); return r; }

__device__ __forceinline__ float rcp(float x) { float r; asm("rcp.approx.ftz.f32 %0, %1;" : "=f"(r) : "f"(x)); return r; }

__device__ __forceinline__ uint32_t gtime() { uint32_t t; asm volatile("mov.u32 %0, %globaltimer_lo;" : "=r"(t)::"memory"); return t; }
__device__ __forceinline__ void sleep_ns(uint32_t ns) {
    uint32_t t0, t;
    asm volatile("mov.u32 %0, %clock;" : "=r"(t0));
    do { __nanosleep(200); asm volatile("mov.u32 %0, %clock;" : "=r"(t)); } while (t - t0 < 2 * ns);
}

__device__ __forceinline__ void ll_store2(ulonglong2* p, float a, float b, uint32_t tag) {
    unsigned long long x = ((unsigned long long)tag << 32) | __float_as_uint(a);
    unsigned long long y = ((unsigned long long)tag << 32) | __float_as_uint(b);
    asm volatile("st.relaxed.gpu.global.v2.b64 [%0], {%1,%2};" ::"l"(p), "l"(x), "l"(y) : "memory");
}
__device__ __forceinline__ void ll_ld2(const void* p, unsigned long long& x, unsigned long long& y) {
    asm volatile("ld.relaxed.gpu.global.v2.b64 {%0,%1}, [%2];" : "=l"(x), "=l"(y) : "l"(p) : "memory");
}
__device__ __forceinline__ void ll_gather4(const ulonglong2* p, uint32_t tag, float& r0, float& r1) {
    unsigned long long x[4], y[4]; uint32_t it = 0;
    while (true) {
        bool ok = true;
#pragma unroll
        for (int k = 0; k < 4; k++) ll_ld2(p + k * 128, x[k], y[k]);
#pragma unroll
        for (int k = 0; k < 4; k++) ok = ok && (uint32_t)(x[k] >> 32) == tag && (uint32_t)(y[k] >> 32) == tag;
        if (ok) break;
        if (++it > SPIN_MAX) __trap();
        __nanosleep(BACKOFF);
    }
    r0 = (__uint_as_float((uint32_t)x[0]) + __uint_as_float((uint32_t)x[1])) + (__uint_as_float((uint32_t)x[2]) + __uint_as_float((uint32_t)x[3]));
    r1 = (__uint_as_float((uint32_t)y[0]) + __uint_as_float((uint32_t)y[1])) + (__uint_as_float((uint32_t)y[2]) + __uint_as_float((uint32_t)y[3]));
}
__device__ __forceinline__ void cnt_rendezvous(unsigned* c, uint32_t target, int tsk) {
    TS(tsk);
    asm volatile("red.release.gpu.global.add.u32 [%0], 1;" ::"l"(c) : "memory");
    if (tsk == 18) TS(tsk + 1);
    uint32_t v, it = 0;
    while (true) {
        asm volatile("ld.acquire.gpu.global.u32 %0, [%1];" : "=r"(v) : "l"(c) : "memory");
        if ((int)(v - target) >= 0) break;
        if (++it > SPIN_MAX) __trap();
        __nanosleep(BACKOFF_RV);
    }
    asm volatile("fence.proxy.async.global;" ::: "memory");
}

__device__ __forceinline__ void matvec_loadA(uint32_t (&a)[8][4], uint32_t tile, uint32_t bar, int w, int lane) {
    const int i = lane >> 3, rr = lane & 7, chunk = 2 * w + (i & 1);
    const uint32_t a0 = tile + (chunk >> 3) * 8192 + (rr + 8 * (i >> 1)) * 128 + (((chunk & 7) ^ rr) << 4);
#pragma unroll
    for (int hh = 0; hh < 2; hh++) {
        mbar_wait(bar + hh * 8, 0);
#pragma unroll
        for (int k = 0; k < 4; k++) ldsm4t(a[hh * 4 + k], a0 + hh * CH + k * 2048);
    }
}
__device__ __forceinline__ void matvec_mma(float (&c)[4], const uint32_t (&a)[8][4], uint32_t vec, int nvec, int lane) {
    const uint32_t va = vec + (lane & (nvec - 1)) * VROW + (lane >> 3) * 16;
    float d[4][4];
#pragma unroll
    for (int q = 0; q < 4; q++) {
        uint32_t b[4];
        ldsm4(b, va + q * 64);
        d[q][0] = d[q][1] = d[q][2] = d[q][3] = 0.f;
        mma(d[q], a[2 * q], b[0], b[1]);
        mma(d[q], a[2 * q + 1], b[2], b[3]);
    }
#pragma unroll
    for (int k = 0; k < 4; k++) c[k] = (d[0][k] + d[1][k]) + (d[2][k] + d[3][k]);
}
__device__ __forceinline__ void matvecT(float (&c)[4], uint32_t tile, uint32_t vec, int nvec, uint32_t bar, int w, int lane) {
    uint32_t a[8][4];
    matvec_loadA(a, tile, bar, w, lane);
    matvec_mma(c, a, vec, nvec, lane);
}
template <class T> __device__ __forceinline__ T* pin(T* p) { asm volatile("" : "+l"(p)); return p; }
__device__ __forceinline__ void post(uint32_t* p, float v) {
    asm volatile("red.relaxed.gpu.global.add.u32 [%0], %1;" ::"l"(p), "r"(~__float_as_uint(v)) : "memory");
}
__device__ __forceinline__ void ld4_if(const void* p, uint4& x, bool need) {
    asm volatile("{\n.reg .pred q;\nsetp.ne.u32 q, %5, 0;\n@q ld.relaxed.gpu.global.v4.b32 {%0,%1,%2,%3}, [%4];\n}"
                 : "+r"(x.x), "+r"(x.y), "+r"(x.z), "+r"(x.w) : "l"(p), "r"((uint32_t)need) : "memory");
}
__device__ __forceinline__ void merge_store(const uint4 (&x)[5], uint32_t dst) {
#pragma unroll
    for (int b = 0; b < 2; b++) {
        const float l0 = __uint_as_float(~(b ? x[4].z : x[4].x)), l1 = __uint_as_float(~(b ? x[4].w : x[4].y));
        const float mx = fmaxf(l0, l1), e0 = ex2(l0 - mx), e1 = ex2(l1 - mx), r = rcp(e0 + e1);
        const uint4 u = x[2 * b], v = x[2 * b + 1];
        const uint32_t lo = pack2((e0 * __uint_as_float(~u.x) + e1 * __uint_as_float(~v.x)) * r, (e0 * __uint_as_float(~u.y) + e1 * __uint_as_float(~v.y)) * r);
        const uint32_t hi = pack2((e0 * __uint_as_float(~u.z) + e1 * __uint_as_float(~v.z)) * r, (e0 * __uint_as_float(~u.w) + e1 * __uint_as_float(~v.w)) * r);
        asm volatile("st.shared.v2.b32 [%0], {%1,%2};" ::"r"(dst + b * YROW), "r"(lo), "r"(hi) : "memory");
    }
}

__global__ void __launch_bounds__(NTHREADS, 1)
fused_decode_kernel(const char* __restrict__ wqraw, Scratch* const sc, const __nv_bfloat16* __restrict__ xA, const __nv_bfloat16* __restrict__ xB,
                    const char* __restrict__ Kc, const char* __restrict__ Vc, const __grid_constant__ Maps maps,
                    const char* __restrict__ woA, const char* __restrict__ woB, __nv_bfloat16* __restrict__ out, const uint32_t zero) {
    unsigned* const cnt = sc->cnt;
    asm volatile("{\n.reg .pred p;\nsetp.eq.u32 p, %1, 0;\n@p cp.async.bulk.prefetch.L2.global [%0], %2;\n}"
                 ::"l"(wqraw + (size_t)blockIdx.x * (2 * CH)), "r"(threadIdx.x), "n"(CH) : "memory");
    extern __shared__ char smem_raw[];
    const uint32_t sm = ((uint32_t)__cvta_generic_to_shared(smem_raw) + 1023u) & ~1023u;
    if (threadIdx.x == 64) {
        unsigned epoch;
        asm volatile("atom.relaxed.gpu.global.add.u32 %0, [%1], 1;" : "=r"(epoch) : "l"(cnt) : "memory");
        sts32(sm + OFF_TAG, (epoch >> 7) + 1u);
    }
    const uint32_t bars = sm + OFF_BAR;
    const int cta = blockIdx.x, h = cta >> 2, j = cta & 3;
    uint64_t pol = 0;
    if (threadIdx.x == 0) {
        TS(0);
        asm volatile("createpolicy.fractional.L2::evict_first.b64 %0, 1.0;" : "=l"(pol));
#pragma unroll
        for (int i = 0; i < WIN; i++) mbar_init(bars + (B_WQB + i) * 8, 1);
        asm volatile("fence.mbarrier_init.release.cluster;" ::: "memory");
#pragma unroll
        for (int i = 0; i < WIN; i++) {
            mbar_expect(bars + (B_WQB + i) * 8, CH);
            tma3d(sm + OFF_S0 + i * CH, &maps.wqB + (i >> 1), j * 128 + (i & 1) * 64, h * 2, bars + (B_WQB + i) * 8, pol);
        }
    }
    const int tid = threadIdx.x < 64 ? threadIdx.x + 384 : threadIdx.x - 64, warp = tid >> 5, lane = tid & 31;

    if (warp == 12) {
        const size_t kvoff = ((size_t)(((j >> 1) * 32 + h) * 4096 + (j & 1) * 2048)) * 256;
        const char* kp = Kc + kvoff;
        const char* vp = Vc + kvoff;
        __syncwarp();
        bar_arrive(0, NTHREADS);
        bar_sync(3, 64);
        if (lane == 0) {
            uint32_t pb[WHI];
#pragma unroll
            for (int i = 0; i < WHI; i++) pb[i] = i < WHI - WIN ? (bars + B_WO * 8) | 1u : bars + (B_WQB + i - (WHI - WIN)) * 8;
            auto pace = [&](uint32_t bar, uint32_t par) {
                uint32_t it = 0;
                while (true) {
                    const uint32_t win = ldsv(sm + OFF_WIN);
                    uint32_t busy = 0;
#pragma unroll
                    for (int i = 0; i < WHI; i++) busy += mbar_test(pb[i] & ~1u, pb[i] & 1u) ^ 1u;
                    if (busy < win) break;
                    if (++it > SPIN_MAX) __trap();
                }
#pragma unroll
                for (int i = 0; i + 1 < WHI; i++) pb[i] = pb[i + 1];
                pb[WHI - 1] = bar | par;
            };
            auto side = [&](const CUtensorMap* m, uint32_t dst, int bidx, int c1, int c2) {
                const uint32_t bar = bars + bidx * 8;
                pace(bar, 0);
                mbar_expect(bar, CH);
                tma3d(dst, m, c1, c2, bar, pol);
            };
#pragma unroll 1
            for (int i = WIN; i < 6; i++)
                side(&maps.wqB + (i >> 1), sm + OFF_S0 + i * CH, B_WQB + i, j * 128 + (i & 1) * 64, h * 2);
            TS(1);
            uint32_t slot = 0, use = 0;
            int nuv = 0;
#pragma unroll 1
            for (int n = 0; n < 2 * NTILE; n++) {
                if (n == RING) {
                    mbar_wait(bars + B_FREE * 8, 0);
#pragma unroll 1
                    for (int q = 0; q < 4; q++) side(&maps.ckv, sm + OFF_S0 + q * CH, B_CKV + q, cta * 64 + q * 16, 0);
                }
                if (nuv < 2 && n > RING && (n >= 2 * NTILE - 8 || mbar_test(bars + B_FREE * 8, 1))) {
                    mbar_wait(bars + B_FREE * 8, 1);
                    side(&maps.wuv, sm + OFF_S1 + nuv * CH, B_WUV + nuv, j * 128 + nuv * 64, h * 2);
                    nuv++;
                }
                const uint32_t fb = bars + slot * 8;
                pace(fb, use & 1);
                mbar_wait(fb + B_EMPTY * 8, (use & 1) ^ 1);
                mbar_expect(fb, CH);
                bulk1d(sm + OFF_RING + slot * CH, ((n & 1) ? vp : kp) + (size_t)(n >> 1) * CH, fb, pol);
                if (n >= FINE_V || (n & 1)) {
                    asm volatile("red.relaxed.gpu.global.add.u32 [%0], %1;" ::"l"(cnt + 3), "r"(n >= FINE_V ? 1 : 2) : "memory");
                    stsv(sm + OFF_NOW, n + 1);
                }
                if (++slot == RING) { slot = 0; use++; }
            }
            TS(2);
            mbar_wait(bars + B_FREE * 8, 0);
            const char* wp = ((cta & 1) ? woB : woA) + ((cta >> 4) * 512 + (cta >> 1 & 7) * 8) * 1024;
            uint32_t it = 0;
#pragma unroll 1
            for (int q = 0; q <= 8; q++) {
                const uint32_t bar = bars + (B_WO + q - 1) * 8;
                if (q) mbar_expect(bar, CH / 2);
                while (true) {
                    const uint32_t t0 = ldsv(sm + OFF_TBOX);
                    if (t0 && gtime() - t0 + 16384u >= 16384u + q * BOX_NS) break;
                    if (++it > SPIN_MAX) __trap();
                }
                if (q < 8) asm volatile("cp.async.bulk.prefetch.L2.global.L2::cache_hint [%0], %1, %2;" ::"l"(wp + q * 65536), "n"(CH / 2), "l"(pol) : "memory");
                if (q) tma3d(sm + OFF_S0 + (q - 1) * (CH / 2), &maps.woA + (cta & 1), (cta >> 4) * 512 + (q - 1) * 64, (cta >> 1) & 7, bar, pol);
            }
            TS(3);
        }
    } else if (warp == 13) {
        if (lane == 0) {
#pragma unroll
            for (int i = 0; i < NBAR; i++)
                if (i < B_WQB || i >= B_WQB + WIN)
                    mbar_init(bars + i * 8, i == B_FREE ? 8 : (i >= B_EMPTY && i < B_EMPTY + RING) ? 4 : 1);
            asm volatile("fence.mbarrier_init.release.cluster;" ::: "memory");
#pragma unroll
            for (int i = 2; i < 8; i++) asm volatile("prefetch.tensormap [%0];" ::"l"(&maps.wqB + i) : "memory");
            stsv(sm + OFF_NOW, 0); stsv(sm + OFF_WIN, WIN); stsv(sm + OFF_TBOX, 0);
        }
        __syncwarp();
        bar_arrive(3, 64);
        bar_sync(0, NTHREADS);
        if (lane == 0) {
            const uint32_t base = (lds32(sm + OFF_TAG) - 1u) * (NCTA * 2 * NTILE);
            mbar_wait(bars + (B_WUK + 1) * 8, 0);
            uint32_t it = 0, tbox = 0;
            while (true) {
                const uint32_t n = ldsv(sm + OFF_NOW);
                uint32_t v;
                asm volatile("ld.relaxed.gpu.global.u32 %0, [%1];" : "=r"(v) : "l"(cnt + 3) : "memory");
                v -= base;
                if (v >= NCTA * EST_FROM && (v <= NCTA * EST_TO || !tbox)) {
                    const uint32_t est = (gtime() + (NCTA * 2 * NTILE - v) * BOX_NS / 64 + (uint32_t)(BOX_SHIFT + (~cta & 1) * (BOX_NS / 2))) | 1u;
                    if (!tbox || (int)(est - tbox) < 0) { tbox = est; stsv(sm + OFF_TBOX, est); }
                }
                if (v >= NCTA * 2 * NTILE - GATE_W) break;
                const int diff = (int)(n * NCTA) - (int)v;
                stsv(sm + OFF_WIN, diff < -THETA ? WHI : WIN - (diff > THETA) - (v >= NCTA * END_V));
                if (++it > SPIN_MAX) __trap();
                __nanosleep(v < NCTA * FINE_V ? BACKOFF3 : BACKOFF2);
            }
            stsv(sm + OFF_WIN, WHI);
            TS(24);
        }
    } else if (warp < 4) {
        const int g = lane >> 2, t = lane & 3, i = lane >> 3, rr = lane & 7;
        bar_sync(0, NTHREADS);
        const uint32_t tag = lds32(sm + OFF_TAG);
        {
            mbar_wait(bars + 8, 0);
            float q0, q1;
            ll_gather4(&sc->e1[0][h * 4][tid], tag, q0, q1);
            sts16(sm + OFF_QB + tid * 2, f2bf((j >> 1) ? q1 : q0));
        }
        bar_sync(1, 128);
        if (tid == 0) TS(4);
        uint32_t qf[8][2];
#pragma unroll
        for (int c = 0; c < 8; c++) {
            const uint32_t a = sm + OFF_QB + (((c + g) & 7) * 8 + 2 * t) * 2;
            qf[c][0] = lds32(a); qf[c][1] = lds32(a + 128);
        }
        float acc[8][4];
#pragma unroll
        for (int c = 0; c < 8; c++) { acc[c][0] = acc[c][1] = acc[c][2] = acc[c][3] = 0.f; }
        float m = -INFINITY, l = 0.f;
        const bool diag = (t == (g >> 1));
        const uint32_t krow = sm + OFF_RING + (warp * 16 + rr + 8 * (i & 1)) * 256 + (i >> 1) * 128;
        const uint32_t vrow = sm + OFF_RING + (warp * 16 + rr + 8 * (i >> 1)) * 256 + (i & 1) * 128;
        uint32_t slot = 0, ph = 0;
        uint32_t* const e5own = pin(&sc->e5[cta][tid]);
        uint32_t a[8][4], b0, b1;
#pragma unroll 1
        for (int tile = 0;; tile++) {
            mbar_wait(bars + slot * 8, ph);
#pragma unroll
            for (int c = 0; c < 8; c++) ldsm4(a[c], krow + slot * CH + (((c + rr) & 7) << 4));
            __syncwarp();
            if (lane == 0) mbar_arrive(bars + (B_EMPTY + slot) * 8 + ((a[0][0] | a[1][0] | a[2][0] | a[3][0] | a[4][0] | a[5][0] | a[6][0] | a[7][0]) & zero));
            if (++slot == RING) { slot = 0; ph ^= 1; }
            float s0[4] = {0.f, 0.f, 0.f, 0.f}, s1[4] = {0.f, 0.f, 0.f, 0.f};
#pragma unroll
            for (int c = 0; c < 8; c += 2) { mma(s0, a[c], qf[c][0], qf[c][1]); mma(s1, a[c + 1], qf[c + 1][0], qf[c + 1][1]); }
            float slo = (g & 1) ? s0[1] + s1[1] : s0[0] + s1[0];
            float shi = (g & 1) ? s0[3] + s1[3] : s0[2] + s1[2];
            slo = diag ? bfround(bfround(slo) * SCALE) : -INFINITY;
            shi = diag ? bfround(bfround(shi) * SCALE) : -INFINITY;
            int key = __float_as_int(fmaxf(slo, shi));
            key ^= (key >> 31) & 0x7fffffff;
            key = __reduce_max_sync(0xffffffffu, key);
            key ^= (key >> 31) & 0x7fffffff;
            const float mn = fmaxf(m, __int_as_float(key));
            const float alpha = ex2((m - mn) * LOG2E);
            m = mn;
            const float plo = ex2((slo - mn) * LOG2E), phi = ex2((shi - mn) * LOG2E);
            l = l * alpha + (plo + phi);
            b0 = (g & 1) ? pack2(0.f, plo) : pack2(plo, 0.f);
            b1 = (g & 1) ? pack2(0.f, phi) : pack2(phi, 0.f);
#pragma unroll
            for (int c = 0; c < 8; c++) { acc[c][0] *= alpha; acc[c][1] *= alpha; acc[c][2] *= alpha; acc[c][3] *= alpha; }
            if (tile == NTILE - 1) break;
            mbar_wait(bars + slot * 8, ph);
#pragma unroll
            for (int c = 0; c < 8; c++) ldsm4t(a[c], vrow + slot * CH + (((c + rr) & 7) << 4));
            __syncwarp();
            if (lane == 0) mbar_arrive(bars + (B_EMPTY + slot) * 8 + ((a[0][0] | a[1][0] | a[2][0] | a[3][0] | a[4][0] | a[5][0] | a[6][0] | a[7][0]) & zero));
            if (++slot == RING) { slot = 0; ph ^= 1; }
#pragma unroll
            for (int c = 0; c < 8; c++) mma(acc[c], a[c], b0, b1);
        }
#pragma unroll
        for (int o = 16; o; o >>= 1) l += __shfl_xor_sync(0xffffffffu, l, o);
        if (lane == 0) stsf2(sm + OFF_ML + warp * 8, m, l);
        mbar_wait(bars + B_S2 * 8, 0);
        bar_sync(1, 128);
        {
            const uint4 ml0 = lds128(sm + OFF_ML), ml1 = lds128(sm + OFF_ML + 16);
            const float m0 = __uint_as_float(ml0.x), m1 = __uint_as_float(ml0.z), m2 = __uint_as_float(ml1.x), m3 = __uint_as_float(ml1.z);
            const float M = fmaxf(fmaxf(m0, m1), fmaxf(m2, m3));
            const float L = (ex2((m0 - M) * LOG2E) * __uint_as_float(ml0.y) + ex2((m1 - M) * LOG2E) * __uint_as_float(ml0.w))
                          + (ex2((m2 - M) * LOG2E) * __uint_as_float(ml1.y) + ex2((m3 - M) * LOG2E) * __uint_as_float(ml1.w));
            const float f = ex2((m - M) * LOG2E) * rcp(L);
            if (tid == 0) post(e5own + (NCTA - cta) * 128 + cta, M * LOG2E + lg2(L));
            mbar_wait(bars + slot * 8, ph);
#pragma unroll
            for (int c = 0; c < 8; c++) ldsm4t(a[c], vrow + slot * CH + (((c + rr) & 7) << 4));
#pragma unroll
            for (int c = 0; c < 8; c++) mma(acc[c], a[c], b0, b1);
            if (tid == 0) TS(5);
            float v[2][8];
#pragma unroll
            for (int c = 0; c < 8; c++) { v[0][c] = acc[c][0] + acc[(c + 7) & 7][1]; v[1][c] = acc[c][2] + acc[(c + 7) & 7][3]; }
#pragma unroll
            for (int c = 0; c < 4; c++) { v[0][c] += __shfl_xor_sync(0xffffffffu, v[0][c + 4], 2); v[1][c] += __shfl_xor_sync(0xffffffffu, v[1][c + 4], 2); }
            const int src = (lane & ~3) | ((lane + 3) & 3);
#pragma unroll
            for (int c = 0; c < 2; c++) { v[0][c] += __shfl_sync(0xffffffffu, v[0][c + 2], src); v[1][c] += __shfl_sync(0xffffffffu, v[1][c + 2], src); }
            const uint32_t wa = sm + OFF_S2 + (warp * 160 + 16 * t + 8 * (t >> 1) + g) * 4;
            sts32(wa, __float_as_uint(v[0][0] * f)); sts32(wa + 32, __float_as_uint(v[0][1] * f));
            sts32(wa + 320, __float_as_uint(v[1][0] * f)); sts32(wa + 352, __float_as_uint(v[1][1] * f));
            bar_sync(1, 128);
            const uint32_t ra = sm + OFF_S2 + (tid + warp * 8) * 4;
            post(e5own, (ldsf(ra) + ldsf(ra + 640)) + (ldsf(ra + 1280) + ldsf(ra + 1920)));
        }
        if (tid == 0) TS(6);
        if (cta & 1) {
            const int c0 = (cta & ~15) + warp * 4;
            const uint32_t* p = e5own + ((c0 - cta) * 128 + lane * 4 - tid);
            const uint32_t* pl = e5own + ((NCTA - cta) * 128 + c0 - tid);
            uint4 x[5];
            bool need[5] = {true, true, true, true, true};
            uint32_t it = 0;
            while (true) {
#pragma unroll
                for (int q = 0; q < 5; q++) ld4_if(q < 4 ? p + q * 128 : pl, x[q], need[q]);
#pragma unroll
                for (int q = 0; q < 5; q++) need[q] = !x[q].x || !x[q].y || !x[q].z || !x[q].w;
                if (!__any_sync(0xffffffffu, need[0] | need[1] | need[2] | need[3] | need[4])) break;
                if (++it > SPIN_MAX) __trap();
            }
            merge_store(x, sm + OFF_Y + warp * YHEAD + lane * 8);
            bar_arrive(4, 256 + 128);
        }
        if (tid == 0) TS(16);
    } else {
        const int st = tid - 128, w = warp - 4;
        const int g = lane >> 2, t = lane & 3, i = lane >> 3, rr = lane & 7;
        if (st < 64) {
            const int which = st >> 5, b = (st >> 4) & 1, c = st & 15;
            const uint4 v = __ldg((const uint4*)((which ? xA : xB) + b * 512 + j * 128) + c);
            sts128(sm + OFF_XB + (which * 2 + b) * VROW + c * 16, v);
        }
        bar_sync(0, NTHREADS);
        const uint32_t tag = lds32(sm + OFF_TAG);
        float c[4];
#pragma unroll 1
        for (int which = 0; which < 2; which++) {
            matvecT(c, sm + OFF_S0 + which * 2 * CH, sm + OFF_XB + which * 2 * VROW, 2, bars + (B_WQB + which * 2) * 8, w, lane);
            if (t == 0) {
                ll_store2(&sc->e1[which][cta][w * 16 + g], c[0], c[1], tag);
                ll_store2(&sc->e1[which][cta][w * 16 + g + 8], c[2], c[3], tag);
            }
        }
        __syncwarp();
        if (lane == 0) mbar_arrive(bars + B_FREE * 8);
        if (st == 0) TS(8);
        if (st < 128) {
            float q0, q1;
            sleep_ns(POLL_DELAY);
            ll_gather4(&sc->e1[1][h * 4][st], tag, q0, q1);
            sts16(sm + OFF_QA + st * 2, f2bf(q0)); sts16(sm + OFF_QA + VROW + st * 2, f2bf(q1));
        }
        bar_sync(2, 256);
        if (st == 0) TS(9);
        {
            const int row = w * 16 + rr + 8 * (i & 1);
            const uint32_t a0 = sm + OFF_S2 + (row >> 6) * CH + (row & 63) * 128;
            const uint32_t va = sm + OFF_QA + g * VROW + t * 4;
            float d[4] = {0.f, 0.f, 0.f, 0.f};
            c[0] = c[1] = c[2] = c[3] = 0.f;
            mbar_wait(bars + (B_WUK + (w >> 2)) * 8, 0);
#pragma unroll
            for (int ks = 0; ks < 8; ks++) {
                const int chunk = 2 * ks + (i >> 1);
                uint32_t a[4];
                ldsm4(a, a0 + (chunk >> 3) * 8192 + (((chunk & 7) ^ rr) << 4));
                const uint32_t b0 = (g < 2) ? lds32(va + ks * 32) : 0u, b1 = (g < 2) ? lds32(va + ks * 32 + 16) : 0u;
                if (ks & 1) mma(d, a, b0, b1); else mma(c, a, b0, b1);
            }
            if (t == 0) {
                const uint32_t qs = sm + OFF_QS + (w * 16 + g) * 2;
                sts16(qs, f2bf(c[0] + d[0])); sts16(qs + VROW, f2bf(c[1] + d[1]));
                sts16(qs + 16, f2bf(c[2] + d[2])); sts16(qs + VROW + 16, f2bf(c[3] + d[3]));
            }
            bar_sync(2, 256);
            if (w == 0) {
                const int b = lane >> 4, cc = lane & 15;
                sc->qabs[(b * 32 + h) * 64 + ((j * 16 + cc) ^ (h & 7))] = lds128(sm + OFF_QS + b * VROW + cc * 16);
                __syncwarp();
                if (lane == 0) {
                    cnt_rendezvous(cnt + 1, tag * 128u, 18);
                    TS(10);
                    mbar_expect(bars + B_GATH * 8, 2 * CH);
                    bulk1d_n(sm + OFF_S2, sc->qabs + (cta >> 6) * 2048, 2 * CH, bars + B_GATH * 8);
                }
                __syncwarp();
            }
        }
        mbar_wait(bars + B_GATH * 8, 0);
        if (st == 0) TS(11);
        {
            const int mt = w & 1, kg = w >> 1;
            const uint32_t qa = sm + OFF_S2 + (mt * 16 + rr + 8 * (i & 1)) * 1024;
            const uint32_t ka = sm + OFF_S0 + kg * CH + (rr + 8 * (i >> 1)) * 128;
            float s0[4] = {0.f, 0.f, 0.f, 0.f}, s1[4] = {0.f, 0.f, 0.f, 0.f};
            mbar_wait(bars + (B_CKV + kg) * 8, 0);
#pragma unroll 2
            for (int gq = 0; gq < 8; gq++) {
#pragma unroll
                for (int k4 = 0; k4 < 4; k4++) {
                    uint32_t a[4], b[4];
                    ldsm4(a, qa + gq * 128 + (((2 * k4 + (i >> 1)) ^ rr) << 4));
                    ldsm4(b, ka + gq * 2048 + (((2 * k4 + (i & 1)) ^ rr) << 4));
                    mma(s0, a, b[0], b[1]);
                    mma(s1, a, b[2], b[3]);
                }
            }
            const uint32_t sa = sm + OFF_SC + ((mt * 16 + g) * 68 + kg * 16 + 2 * t) * 4;
            stsf2(sa, s0[0], s0[1]); stsf2(sa + 32, s1[0], s1[1]);
            stsf2(sa + 8 * 68 * 4, s0[2], s0[3]); stsf2(sa + 8 * 68 * 4 + 32, s1[2], s1[3]);
        }
        bar_sync(2, 256);
        {
            const int head = w * 4 + i;
            const uint32_t sa = sm + OFF_SC + (head * 68 + rr * 8) * 4;
            const uint4 u0 = lds128(sa), u1 = lds128(sa + 16);
            float s[8] = {__uint_as_float(u0.x), __uint_as_float(u0.y), __uint_as_float(u0.z), __uint_as_float(u0.w),
                          __uint_as_float(u1.x), __uint_as_float(u1.y), __uint_as_float(u1.z), __uint_as_float(u1.w)};
            float mx = s[0];
#pragma unroll
            for (int k = 1; k < 8; k++) mx = fmaxf(mx, s[k]);
#pragma unroll
            for (int o = 1; o < 8; o <<= 1) mx = fmaxf(mx, __shfl_xor_sync(0xffffffffu, mx, o));
            float sum = 0.f;
#pragma unroll
            for (int k = 0; k < 8; k++) { s[k] = ex2((s[k] - mx) * (SCALE * LOG2E)); sum += s[k]; }
#pragma unroll
            for (int o = 1; o < 8; o <<= 1) sum += __shfl_xor_sync(0xffffffffu, sum, o);
            const float inv = __fdividef(1.f, sum);
            uint4 p;
            p.x = pack2(s[0] * inv, s[1] * inv); p.y = pack2(s[2] * inv, s[3] * inv);
            p.z = pack2(s[4] * inv, s[5] * inv); p.w = pack2(s[6] * inv, s[7] * inv);
            sts128(sm + OFF_P + head * 128 + ((rr ^ (head & 7)) << 4), p);
            if (rr == 0) ((float*)sc->lse)[head * 128 + cta] = mx * (SCALE * LOG2E) + lg2(sum);
        }
        bar_sync(2, 256);
        {
            float o[2][8][4];
#pragma unroll
            for (int mt = 0; mt < 2; mt++)
#pragma unroll
                for (int n = 0; n < 8; n++) { o[mt][n][0] = o[mt][n][1] = o[mt][n][2] = o[mt][n][3] = 0.f; }
            const uint32_t pa = sm + OFF_P + (rr + 8 * (i & 1)) * 128;
            const uint32_t va = sm + OFF_S0 + w * 2048 + (rr + 8 * (i & 1)) * 128;
#pragma unroll 1
            for (int kq = 0; kq < 4; kq++) {
                uint32_t a0[4], a1[4];
                ldsm4(a0, pa + (((2 * kq + (i >> 1)) ^ rr) << 4));
                ldsm4(a1, pa + 2048 + (((2 * kq + (i >> 1)) ^ rr) << 4));
#pragma unroll
                for (int n = 0; n < 8; n += 2) {
                    uint32_t b[4];
                    ldsm4t(b, va + kq * CH + (((n + (i >> 1)) ^ rr) << 4));
                    mma(o[0][n], a0, b[0], b[1]); mma(o[1][n], a1, b[0], b[1]);
                    mma(o[0][n + 1], a0, b[2], b[3]); mma(o[1][n + 1], a1, b[2], b[3]);
                }
            }
#pragma unroll
            for (int mt = 0; mt < 2; mt++)
#pragma unroll
                for (int hf = 0; hf < 2; hf++) {
                    const uint32_t dst = sm + OFF_S2 + (mt * 16 + hf * 8 + g) * 1024 + w * 128 + t * 16;
#pragma unroll
                    for (int nb = 0; nb < 2; nb++) {
                        uint4 v;
                        v.x = pack2(o[mt][nb * 4 + 0][hf * 2], o[mt][nb * 4 + 0][hf * 2 + 1]);
                        v.y = pack2(o[mt][nb * 4 + 1][hf * 2], o[mt][nb * 4 + 1][hf * 2 + 1]);
                        v.z = pack2(o[mt][nb * 4 + 2][hf * 2], o[mt][nb * 4 + 2][hf * 2 + 1]);
                        v.w = pack2(o[mt][nb * 4 + 3][hf * 2], o[mt][nb * 4 + 3][hf * 2 + 1]);
                        sts128(dst + nb * 64, v);
                    }
                }
            asm volatile("fence.proxy.async.shared::cta;" ::: "memory");
            __syncwarp();
            if (lane == 0) mbar_arrive(bars + B_FREE * 8);
            sc->e4[cta][st] = 0u;
            if (st < 128) sc->e5[cta][st] = 0u;
            else if (cta == 0) sc->e5[NCTA][st - 128] = 0u;
            if (st >= 248) ((uint32_t*)out)[cta * 8 + st - 248] = 0u;
        }
        bar_sync(2, 256);
        if (st == 0) {
            TS(12);
#pragma unroll 1
            for (int k = 0; k < ST_SPLIT; k++) {
                asm volatile("cp.async.bulk.tensor.3d.global.shared::cta.bulk_group [%0, {%2,%3,%4}], [%1];"
                             ::"l"(&maps.ctxp), "r"(sm + OFF_S2 + k * (2 * CH / ST_SPLIT)), "r"(0), "r"(cta), "r"(k * (128 / ST_SPLIT)) : "memory");
                if (k + 1 < ST_SPLIT) __nanosleep(ST_GAP);
            }
            asm volatile("cp.async.bulk.commit_group;" ::: "memory");
            asm volatile("cp.async.bulk.wait_group 0;" ::: "memory");
            cnt_rendezvous(cnt + 2, tag * 128u, 20);
            TS(13);
            mbar_expect(bars + B_GATH * 8, 2 * CH + 512);
            bulk1d_n(sm + OFF_LSE, sc->lse + h * 32, 512, bars + B_GATH * 8);
#pragma unroll 1
            for (int k = 0; k < ST_SPLIT; k++) {
                bulk1d_n(sm + OFF_S2 + k * (2 * CH / ST_SPLIT), sc->ctxp + cta * 2048 + k * (2048 / ST_SPLIT), 2 * CH / ST_SPLIT, bars + B_GATH * 8);
                __nanosleep(LD_GAP);
            }
        }
        __syncwarp();
        {
            mbar_wait(bars + B_GATH * 8, 1);
            if (st == 0) TS(22);
            uint4 v[8];
#pragma unroll
            for (int k = 0; k < 8; k++) v[k] = lds128(sm + OFF_S2 + (k * 256 + st) * 16);
            float ls[4];
#pragma unroll
            for (int k = 0; k < 4; k++) ls[k] = ldsf(sm + OFF_LSE + (k * 32 + lane) * 4);
            float m0 = fmaxf(ls[0], ls[1]), m1 = fmaxf(ls[2], ls[3]);
#pragma unroll
            for (int o = 16; o; o >>= 1) { m0 = fmaxf(m0, __shfl_xor_sync(0xffffffffu, m0, o)); m1 = fmaxf(m1, __shfl_xor_sync(0xffffffffu, m1, o)); }
            ls[0] = ex2(ls[0] - m0); ls[1] = ex2(ls[1] - m0); ls[2] = ex2(ls[2] - m1); ls[3] = ex2(ls[3] - m1);
            float z0 = ls[0] + ls[1], z1 = ls[2] + ls[3];
#pragma unroll
            for (int o = 16; o; o >>= 1) { z0 += __shfl_xor_sync(0xffffffffu, z0, o); z1 += __shfl_xor_sync(0xffffffffu, z1, o); }
            z0 = __fdividef(1.f, z0); z1 = __fdividef(1.f, z1);
            ls[0] *= z0; ls[1] *= z0; ls[2] *= z1; ls[3] *= z1;
            float a[2][8];
#pragma unroll
            for (int e = 0; e < 8; e++) a[0][e] = a[1][e] = 0.f;
            const int rg = st >> 4;
#pragma unroll
            for (int k = 0; k < 8; k++) {
                const float wt = __shfl_sync(0xffffffffu, ls[k >> 1], rg + 16 * (k & 1));
                const uint32_t u[4] = {v[k].x, v[k].y, v[k].z, v[k].w};
#pragma unroll
                for (int e = 0; e < 4; e++) {
                    a[k >> 2][2 * e] += wt * __uint_as_float(u[e] << 16);
                    a[k >> 2][2 * e + 1] += wt * __uint_as_float(u[e] & 0xffff0000u);
                }
            }
            const int b = lane >> 4, u16 = lane & 15;
            const uint32_t ra = sm + OFF_SC + (w * 256 + b * 128 + (u16 >> 3) * 64 + ((u16 >> 2) & 1) * 32 + (u16 & 3) * 2) * 4;
#pragma unroll
            for (int e = 0; e < 8; e += 2) {
                const float k0 = b ? a[1][e] : a[0][e], k1 = b ? a[1][e + 1] : a[0][e + 1];
                const float s0 = b ? a[0][e] : a[1][e], s1 = b ? a[0][e + 1] : a[1][e + 1];
                stsf2(ra + (e >> 1) * 32, k0 + __shfl_xor_sync(0xffffffffu, s0, 16), k1 + __shfl_xor_sync(0xffffffffu, s1, 16));
            }
            bar_sync(2, 256);
            if (st == 0) mbar_arrive(bars + B_S2 * 8);
            float s = 0.f;
#pragma unroll
            for (int k = 0; k < 8; k++) s += ldsf(sm + OFF_SC + (k * 256 + st) * 4);
            const float hi = bfround(s);
            const uint32_t ca = sm + OFF_CC + (st >> 7) * VROW + (st & 127) * 2;
            sts16(ca, f2bf(hi)); sts16(ca + 2 * VROW, f2bf(s - hi));
            bar_sync(2, 256);
        }
        matvecT(c, sm + OFF_S1, sm + OFF_CC, 4, bars + B_WUV * 8, w, lane);
#pragma unroll
        for (int k = 0; k < 4; k++) c[k] += __shfl_xor_sync(0xffffffffu, c[k], 1);
        post(&sc->e4[cta][(t & 1) * 128 + w * 16 + (t >> 1) * 8 + g], t == 0 ? c[0] : t == 1 ? c[1] : t == 2 ? c[2] : c[3]);
        __syncwarp();
        if (lane == 0) mbar_arrive(bars + B_FREE * 8);
        if (st == 0) TS(23);
        if (st < 128) sts32(sm + OFF_PAIR + st * 4, EMPTY);
        if (!(cta & 1)) {
            const uint32_t* p = &sc->e4[(cta & ~15) + (w >> 1) * 4][(w & 1) * 128 + lane * 4];
            uint4 x[4];
            bool need[4] = {true, true, true, true};
            uint32_t it = 0;
            sleep_ns(POLL_DELAY2);
            while (true) {
#pragma unroll
                for (int q = 0; q < 4; q++) ld4_if(p + q * 256, x[q], need[q]);
#pragma unroll
                for (int q = 0; q < 4; q++) need[q] = !x[q].x || !x[q].y || !x[q].z || !x[q].w;
                if (!__any_sync(0xffffffffu, need[0] | need[1] | need[2] | need[3])) break;
                if (++it > SPIN_MAX) __trap();
                __nanosleep(BACKOFF);
            }
            auto sum4 = [](uint32_t a, uint32_t b, uint32_t c, uint32_t d) {
                return (__uint_as_float(~a) + __uint_as_float(~b)) + (__uint_as_float(~c) + __uint_as_float(~d));
            };
            asm volatile("st.shared.v2.b32 [%0], {%1,%2};" ::"r"(sm + OFF_Y + (w & 1) * YROW + (w >> 1) * YHEAD + lane * 8),
                         "r"(pack2(sum4(x[0].x, x[1].x, x[2].x, x[3].x), sum4(x[0].y, x[1].y, x[2].y, x[3].y))),
                         "r"(pack2(sum4(x[0].z, x[1].z, x[2].z, x[3].z), sum4(x[0].w, x[1].w, x[2].w, x[3].w))) : "memory");
        }
        if (st == 0) TS(14);
        bar_sync(2, 256);
        {
            const int hf = w >> 2, cg = w & 3;
            const uint32_t a0 = sm + OFF_S0 + hf * 8192 + (rr + 8 * (i >> 1)) * 128 + (((2 * cg + (i & 1)) ^ rr) << 4);
            const uint32_t va = sm + OFF_Y + (lane >> 1 & 1) * YROW + (lane & 1) * YHEAD + hf * 128 + i * 16;
            const uint32_t wb = bars + (B_WO + hf) * 8;
            const uint32_t pa = sm + OFF_PAIR + (cg * 32 + lane) * 4;
            const int col = (t & 1) * 1024 + (cta & 1) * 512 + (cta >> 1 & 7) * 64 + cg * 16 + (t >> 1) * 8 + g;
            __nv_bfloat16* const outp = pin(out + (col & ~1));
            const bool up = t >= 2, odd = g & 1;
            uint32_t a[4][4][4], b[4][4];
            float d[2][4][4];
#pragma unroll
            for (int k = 0; k < 8; k++) d[k >> 2][k & 3][0] = d[k >> 2][k & 3][1] = d[k >> 2][k & 3][2] = d[k >> 2][k & 3][3] = 0.f;
            auto load_w = [&](int hd) {
                mbar_wait(wb + hd * 16, 0);
#pragma unroll
                for (int k = 0; k < 4; k++) ldsm4t(a[hd][k], a0 + hd * CH + k * 2048);
            };
            auto load_y = [&]() {
#pragma unroll
                for (int q = 0; q < 4; q++) ldsm4(b[q], va + (q >> 1) * 2 * YHEAD + (q & 1) * 64);
            };
            auto head = [&](int hd) {
#pragma unroll
                for (int k = 0; k < 4; k++) mma(d[hd & 1][k], a[hd][k], b[(hd & 2) + (k >> 1)][(k & 1) * 2], b[(hd & 2) + (k >> 1)][(k & 1) * 2 + 1]);
            };
            if (cta & 1) {
                load_w(0); load_w(1);
                bar_sync(4, 256 + 128);
                load_y();
                head(0); head(1);
            } else {
                load_y();
                load_w(0); head(0);
                load_w(1); head(1);
            }
            if (st == 0) TS(25);
            load_w(2); head(2);
            float z = up ? (d[0][0][2] + d[0][1][2]) + (d[0][2][2] + d[0][3][2]) : (d[0][0][0] + d[0][1][0]) + (d[0][2][0] + d[0][3][0]);
            mbar_wait_uni(wb + 48);
            if (st == 0) TS(26);
            uint32_t other = ldsv(pa);
#pragma unroll
            for (int k = 0; k < 4; k++) ldsm4t(a[3][k], a0 + 3 * CH + k * 2048);
            head(3);
            z += other != EMPTY ? __uint_as_float(other) : 0.f;
            float z1 = z, z3 = z;
#pragma unroll
            for (int k = 0; k < 3; k++) { z1 += d[1][k][1]; z3 += d[1][k][3]; }
            z = up ? z3 + d[1][3][3] : z1 + d[1][3][1];
            if (st == 0) TS(17);
            asm volatile("{\n.reg .pred p;\nsetp.eq.u32 p, %2, %3;\n@p bra FIRST;\nred.relaxed.gpu.global.add.noftz.bf16x2 [%0], %1;\nexit;\nFIRST:\n}"
                         ::"l"(outp), "r"(odd ? pack2(0.f, z) : pack2(z, 0.f)), "r"(other), "n"(EMPTY) : "memory");
            asm volatile("atom.shared.exch.b32 %0, [%1], %2;" : "=r"(other) : "r"(pa), "r"(__float_as_uint(z)) : "memory");
            z += __uint_as_float(other);
            asm volatile("{\n.reg .pred p;\nsetp.eq.u32 p, %2, %3;\n@p exit;\nred.relaxed.gpu.global.add.noftz.bf16x2 [%0], %1;\n}"
                         ::"l"(outp), "r"(odd ? pack2(0.f, z) : pack2(z, 0.f)), "r"(other), "n"(EMPTY) : "memory");
        }
    }
}

typedef CUresult (*EncodeFn)(CUtensorMap*, CUtensorMapDataType, cuuint32_t, void*, const cuuint64_t*, const cuuint64_t*,
                             const cuuint32_t*, const cuuint32_t*, CUtensorMapInterleave, CUtensorMapSwizzle,
                             CUtensorMapL2promotion, CUtensorMapFloatOOBfill);

void make_map(EncodeFn enc, CUtensorMap* m, void* p, unsigned rows, unsigned cols, unsigned br, unsigned bg) {
    cuuint64_t gd[3] = {64, rows, cols / 64};
    cuuint64_t gs[2] = {(cuuint64_t)cols * 2, 128};
    cuuint32_t bx[3] = {64, br, bg};
    cuuint32_t es[3] = {1, 1, 1};
    enc(m, CU_TENSOR_MAP_DATA_TYPE_BFLOAT16, 3, p, gd, gs, bx, es, CU_TENSOR_MAP_INTERLEAVE_NONE,
        CU_TENSOR_MAP_SWIZZLE_128B, CU_TENSOR_MAP_L2_PROMOTION_L2_128B, CU_TENSOR_MAP_FLOAT_OOB_FILL_NONE);
}

}

extern "C" void kernel_launch(void* const* d_in, const int* in_sizes, int n_in, void* d_out, int out_size) {
    static EncodeFn enc = nullptr;
    if (!enc) {
        void* fn = nullptr;
        cudaDriverEntryPointQueryResult qr;
        cudaGetDriverEntryPoint("cuTensorMapEncodeTiled", &fn, cudaEnableDefault, &qr);
        enc = (EncodeFn)fn;
        cudaFuncSetAttribute(fused_decode_kernel, cudaFuncAttributeMaxDynamicSharedMemorySize, SMEM_BYTES);
    }
    Scratch* sc = nullptr;
    cudaGetSymbolAddress((void**)&sc, g_scratch);
    Maps maps;
    make_map(enc, &maps.wqB, d_in[9], 512, 4096, 64, 2);
    make_map(enc, &maps.wqA, d_in[2], 512, 4096, 64, 2);
    make_map(enc, &maps.wuk, d_in[3], 512, 4096, 64, 2);
    make_map(enc, &maps.wuv, d_in[4], 512, 4096, 64, 2);
    make_map(enc, &maps.woA, d_in[5], 4096, 512, 64, 1);
    make_map(enc, &maps.woB, d_in[10], 4096, 512, 64, 1);
    make_map(enc, &maps.ckv, d_in[1], 8192, 512, 16, 8);
    {
        void* p = sc->ctxp;
        cuuint64_t gd[3] = {128, 128, 128};
        cuuint64_t gs[2] = {256, 32768};
        cuuint32_t bx[3] = {128, 1, 128 / ST_SPLIT};
        cuuint32_t es[3] = {1, 1, 1};
        enc(&maps.ctxp, CU_TENSOR_MAP_DATA_TYPE_BFLOAT16, 3, p, gd, gs, bx, es, CU_TENSOR_MAP_INTERLEAVE_NONE,
            CU_TENSOR_MAP_SWIZZLE_NONE, CU_TENSOR_MAP_L2_PROMOTION_NONE, CU_TENSOR_MAP_FLOAT_OOB_FILL_NONE);
    }
    fused_decode_kernel<<<NCTA, NTHREADS, SMEM_BYTES>>>((const char*)d_in[9], sc, (const __nv_bfloat16*)d_in[0], (const __nv_bfloat16*)d_in[6],
                                                         (const char*)d_in[7], (const char*)d_in[8], maps, (const char*)d_in[5], (const char*)d_in[10],
                                                         (__nv_bfloat16*)d_out, 0u);
}
```

```cpp
#include <cuda_runtime.h>
#include <cuda.h>
#include <cuda_bf16.h>
#include <stdint.h>

#define RING 7
#define WIN 4
#define WHI 5
#define THETA 64
#define END_V 40
#define GATE_W 64
#define BOX_NS 319
#define BOX_SHIFT -25
#define EST_FROM 57
#define EST_TO 62
#define POLL_DELAY 3000
#define POLL_DELAY2 2500
#define ST_SPLIT 8
#define ST_GAP 500
#define LD_GAP 300
#define BACKOFF 200
#define BACKOFF_RV 800
#define FINE_V 52
#define BACKOFF2 100
#define BACKOFF3 300

namespace {

constexpr int NCTA = 128;
constexpr int NTHREADS = 448;
constexpr uint32_t CH = 16384;
constexpr int NTILE = 32;

constexpr uint32_t OFF_RING = 0;
constexpr uint32_t OFF_S0 = RING * CH;
constexpr uint32_t OFF_S1 = OFF_S0 + 2 * CH;
constexpr uint32_t OFF_S2 = OFF_S1 + 2 * CH;
constexpr uint32_t OFF_P = OFF_S2 + 2 * CH;
constexpr uint32_t OFF_SC = OFF_P + 4096;
constexpr uint32_t VROW = 272;
constexpr uint32_t OFF_XB = OFF_SC + 8704;
constexpr uint32_t OFF_XA = OFF_XB + 2 * VROW;
constexpr uint32_t OFF_QA = OFF_XA + 2 * VROW;
constexpr uint32_t OFF_QS = OFF_QA + 2 * VROW;
constexpr uint32_t OFF_CC = OFF_QS + 2 * VROW;
constexpr uint32_t OFF_QB = OFF_CC + 4 * VROW;
constexpr uint32_t YHEAD = 288, YROW = 4 * YHEAD + 16;
constexpr uint32_t OFF_Y = OFF_P;
constexpr uint32_t OFF_PAIR = OFF_P + 2 * YROW;
constexpr uint32_t EMPTY = 0xffffffffu;
constexpr uint32_t OFF_LSE = OFF_QB + 256;
constexpr uint32_t OFF_ML = OFF_LSE + 512;
constexpr uint32_t OFF_TAG = OFF_ML + 32;
constexpr uint32_t OFF_NOW = OFF_TAG + 4;
constexpr uint32_t OFF_WIN = OFF_TAG + 8;
constexpr uint32_t OFF_TBOX = OFF_TAG + 12;
constexpr uint32_t OFF_BAR = OFF_TAG + 16;
constexpr int B_EMPTY = RING;
constexpr int B_WQB = 2 * RING;
constexpr int B_WQA = B_WQB + 2;
constexpr int B_WUK = B_WQA + 2;
constexpr int B_WUV = B_WUK + 2;
constexpr int B_CKV = B_WUV + 2;
constexpr int B_WO = B_CKV + 4;
constexpr int B_FREE = B_WO + 8;
constexpr int B_GATH = B_FREE + 1;
constexpr int B_S2 = B_GATH + 1;
constexpr int NBAR = B_S2 + 1;
constexpr uint32_t TS_OFF = OFF_BAR + NBAR * 8;
constexpr uint32_t SMEM_USED = TS_OFF;
constexpr uint32_t SMEM_BYTES = SMEM_USED + 1024;
static_assert(SMEM_BYTES <= 232448, "smem");
static_assert(RING >= WHI && WHI >= WIN && WIN >= 3 && WIN <= 6 && FINE_V % 2 == 0, "windows");

constexpr float LOG2E = 1.4426950408889634f;
constexpr float SCALE = 0.08838834764831845f;
#define SPIN_LOG 22
constexpr uint32_t SPIN_MAX = 1u << SPIN_LOG;

struct Maps { CUtensorMap wqB, wqA, wuk, wuv, woA, woB, ckv, ctxp; };

struct Scratch {
    unsigned cnt[64];
    ulonglong2 e1[2][NCTA][128];
    uint4 qabs[2 * 32 * 64];
    float4 lse[32 * 32];
    uint32_t e4[NCTA][256];
    uint32_t e5[NCTA + 2][128];
    uint4 ctxp[NCTA * 128 * 16];
};
__device__ __align__(256) Scratch g_scratch;

#define TS(k) do {} while (0)

__device__ __forceinline__ void mbar_init(uint32_t b, int c) { asm volatile("mbarrier.init.shared::cta.b64 [%0], %1;" ::"r"(b), "r"(c) : "memory"); }
__device__ __forceinline__ void mbar_expect(uint32_t b, uint32_t bytes) { asm volatile("mbarrier.arrive.expect_tx.shared::cta.b64 _, [%0], %1;" ::"r"(b), "r"(bytes) : "memory"); }
__device__ __forceinline__ void mbar_arrive(uint32_t b) { asm volatile("mbarrier.arrive.shared::cta.b64 _, [%0];" ::"r"(b) : "memory"); }
__device__ __forceinline__ void mbar_wait(uint32_t b, uint32_t ph) {
    uint32_t ok, it = 0;
    do {
        asm volatile("{\n.reg .pred p;\nmbarrier.try_wait.parity.shared::cta.b64 p, [%1], %2;\nselp.u32 %0, 1, 0, p;\n}" : "=r"(ok) : "r"(b), "r"(ph) : "memory");
        if (++it > SPIN_MAX) __trap();
    } while (!ok);
}
__device__ __forceinline__ void mbar_wait_uni(uint32_t b) {
    asm volatile("{\n.reg .pred p, q;\n.reg .u32 n;\nmov.u32 n, 0;\nAGAIN:\nadd.u32 n, n, 1;\nsetp.gt.u32 q, n, %1;\n"
                 "mbarrier.try_wait.parity.shared::cta.b64 p, [%0], 0;\n@q trap;\n@!p bra.uni AGAIN;\n}" ::"r"(b), "n"(SPIN_MAX) : "memory");
}
__device__ __forceinline__ uint32_t mbar_test(uint32_t b, uint32_t ph) {
    uint32_t ok;
    asm volatile("{\n.reg .pred p;\nmbarrier.test_wait.parity.shared::cta.b64 p, [%1], %2;\nselp.u32 %0, 1, 0, p;\n}" : "=r"(ok) : "r"(b), "r"(ph) : "memory");
    return ok;
}
__device__ __forceinline__ void bulk1d(uint32_t dst, const void* src, uint32_t bar, uint64_t pol) {
    asm volatile("cp.async.bulk.shared::cluster.global.mbarrier::complete_tx::bytes.L2::cache_hint [%0], [%1], %2, [%3], %4;"
                 ::"r"(dst), "l"(src), "n"(CH), "r"(bar), "l"(pol) : "memory");
}
__device__ __forceinline__ void bulk1d_n(uint32_t dst, const void* src, uint32_t bytes, uint32_t bar) {
    asm volatile("cp.async.bulk.shared::cluster.global.mbarrier::complete_tx::bytes [%0], [%1], %2, [%3];"
                 ::"r"(dst), "l"(src), "r"(bytes), "r"(bar) : "memory");
}
__device__ __forceinline__ void tma3d(uint32_t dst, const CUtensorMap* map, int c1, int c2, uint32_t bar, uint64_t pol) {
    asm volatile("cp.async.bulk.tensor.3d.shared::cluster.global.mbarrier::complete_tx::bytes.L2::cache_hint [%0], [%1, {%3,%4,%5}], [%2], %6;"
                 ::"r"(dst), "l"(map), "r"(bar), "r"(0), "r"(c1), "r"(c2), "l"(pol) : "memory");
}
__device__ __forceinline__ void bar_sync(int id, int n) { asm volatile("barrier.cta.sync %0, %1;" ::"r"(id), "r"(n) : "memory"); }
__device__ __forceinline__ void bar_arrive(int id, int n) { asm volatile("barrier.cta.arrive %0, %1;" ::"r"(id), "r"(n) : "memory"); }
__device__ __forceinline__ void ldsm4(uint32_t (&r)[4], uint32_t a) {
    asm volatile("ldmatrix.sync.aligned.m8n8.x4.shared.b16 {%0,%1,%2,%3}, [%4];" : "=r"(r[0]), "=r"(r[1]), "=r"(r[2]), "=r"(r[3]) : "r"(a) : "memory");
}
__device__ __forceinline__ void ldsm4t(uint32_t (&r)[4], uint32_t a) {
    asm volatile("ldmatrix.sync.aligned.m8n8.x4.trans.shared.b16 {%0,%1,%2,%3}, [%4];" : "=r"(r[0]), "=r"(r[1]), "=r"(r[2]), "=r"(r[3]) : "r"(a) : "memory");
}
__device__ __forceinline__ void mma(float (&c)[4], const uint32_t (&a)[4], uint32_t b0, uint32_t b1) {
    asm volatile("mma.sync.aligned.m16n8k16.row.col.f32.bf16.bf16.f32 {%0,%1,%2,%3}, {%4,%5,%6,%7}, {%8,%9}, {%0,%1,%2,%3};"
                 : "+f"(c[0]), "+f"(c[1]), "+f"(c[2]), "+f"(c[3]) : "r"(a[0]), "r"(a[1]), "r"(a[2]), "r"(a[3]), "r"(b0), "r"(b1));
}
__device__ __forceinline__ uint32_t lds32(uint32_t a) { uint32_t v; asm volatile("ld.shared.b32 %0, [%1];" : "=r"(v) : "r"(a) : "memory"); return v; }
__device__ __forceinline__ uint32_t ldsv(uint32_t a) { uint32_t v; asm volatile("ld.volatile.shared.b32 %0, [%1];" : "=r"(v) : "r"(a) : "memory"); return v; }
__device__ __forceinline__ void stsv(uint32_t a, uint32_t v) { asm volatile("st.volatile.shared.b32 [%0], %1;" ::"r"(a), "r"(v) : "memory"); }
__device__ __forceinline__ float ldsf(uint32_t a) { float v; asm volatile("ld.shared.f32 %0, [%1];" : "=f"(v) : "r"(a) : "memory"); return v; }
__device__ __forceinline__ uint4 lds128(uint32_t a) { uint4 v; asm volatile("ld.shared.v4.b32 {%0,%1,%2,%3}, [%4];" : "=r"(v.x), "=r"(v.y), "=r"(v.z), "=r"(v.w) : "r"(a) : "memory"); return v; }
__device__ __forceinline__ void sts16(uint32_t a, uint16_t v) { asm volatile("st.shared.b16 [%0], %1;" ::"r"(a), "h"(v) : "memory"); }
__device__ __forceinline__ void sts32(uint32_t a, uint32_t v) { asm volatile("st.shared.b32 [%0], %1;" ::"r"(a), "r"(v) : "memory"); }
__device__ __forceinline__ void stsf2(uint32_t a, float x, float y) { asm volatile("st.shared.v2.f32 [%0], {%1,%2};" ::"r"(a), "f"(x), "f"(y) : "memory"); }
__device__ __forceinline__ void sts128(uint32_t a, uint4 v) { asm volatile("st.shared.v4.b32 [%0], {%1,%2,%3,%4};" ::"r"(a), "r"(v.x), "r"(v.y), "r"(v.z), "r"(v.w) : "memory"); }
__device__ __forceinline__ uint16_t f2bf(float x) { return __bfloat16_as_ushort(__float2bfloat16_rn(x)); }
__device__ __forceinline__ float bfround(float x) { return __bfloat162float(__float2bfloat16_rn(x)); }
__device__ __forceinline__ uint32_t pack2(float lo, float hi) { uint32_t r; asm("cvt.rn.bf16x2.f32 %0, %1, %2;" : "=r"(r) : "f"(hi), "f"(lo)); return r; }
__device__ __forceinline__ float ex2(float x) { float r; asm("ex2.approx.ftz.f32 %0, %1;" : "=f"(r) : "f"(x)); return r; }
__device__ __forceinline__ float lg2(float x) { float r; asm("lg2.approx.ftz.f32 %0, %1;" : "=f"(r) : "f"(x)); return r; }

__device__ __forceinline__ float rcp(float x) { float r; asm("rcp.approx.ftz.f32 %0, %1;" : "=f"(r) : "f"(x)); return r; }

__device__ __forceinline__ uint32_t gtime() { uint32_t t; asm volatile("mov.u32 %0, %globaltimer_lo;" : "=r"(t)::"memory"); return t; }
__device__ __forceinline__ void sleep_ns(uint32_t ns) {
    uint32_t t0, t;
    asm volatile("mov.u32 %0, %clock;" : "=r"(t0));
    do { __nanosleep(200); asm volatile("mov.u32 %0, %clock;" : "=r"(t)); } while (t - t0 < 2 * ns);
}

__device__ __forceinline__ void ll_store2(ulonglong2* p, float a, float b, uint32_t tag) {
    unsigned long long x = ((unsigned long long)tag << 32) | __float_as_uint(a);
    unsigned long long y = ((unsigned long long)tag << 32) | __float_as_uint(b);
    asm volatile("st.relaxed.gpu.global.v2.b64 [%0], {%1,%2};" ::"l"(p), "l"(x), "l"(y) : "memory");
}
__device__ __forceinline__ void ll_ld2(const void* p, unsigned long long& x, unsigned long long& y) {
    asm volatile("ld.relaxed.gpu.global.v2.b64 {%0,%1}, [%2];" : "=l"(x), "=l"(y) : "l"(p) : "memory");
}
__device__ __forceinline__ void ll_gather4(const ulonglong2* p, uint32_t tag, float& r0, float& r1) {
    unsigned long long x[4], y[4]; uint32_t it = 0;
    while (true) {
        bool ok = true;
#pragma unroll
        for (int k = 0; k < 4; k++) ll_ld2(p + k * 128, x[k], y[k]);
#pragma unroll
        for (int k = 0; k < 4; k++) ok = ok && (uint32_t)(x[k] >> 32) == tag && (uint32_t)(y[k] >> 32) == tag;
        if (ok) break;
        if (++it > SPIN_MAX) __trap();
        __nanosleep(BACKOFF);
    }
    r0 = (__uint_as_float((uint32_t)x[0]) + __uint_as_float((uint32_t)x[1])) + (__uint_as_float((uint32_t)x[2]) + __uint_as_float((uint32_t)x[3]));
    r1 = (__uint_as_float((uint32_t)y[0]) + __uint_as_float((uint32_t)y[1])) + (__uint_as_float((uint32_t)y[2]) + __uint_as_float((uint32_t)y[3]));
}
__device__ __forceinline__ void cnt_rendezvous(unsigned* c, uint32_t target, int tsk) {
    TS(tsk);
    asm volatile("red.release.gpu.global.add.u32 [%0], 1;" ::"l"(c) : "memory");
    if (tsk == 18) TS(tsk + 1);
    uint32_t v, it = 0;
    while (true) {
        asm volatile("ld.acquire.gpu.global.u32 %0, [%1];" : "=r"(v) : "l"(c) : "memory");
        if ((int)(v - target) >= 0) break;
        if (++it > SPIN_MAX) __trap();
        __nanosleep(BACKOFF_RV);
    }
    asm volatile("fence.proxy.async.global;" ::: "memory");
}

__device__ __forceinline__ void matvec_loadA(uint32_t (&a)[8][4], uint32_t tile, uint32_t bar, int w, int lane) {
    const int i = lane >> 3, rr = lane & 7, chunk = 2 * w + (i & 1);
    const uint32_t a0 = tile + (chunk >> 3) * 8192 + (rr + 8 * (i >> 1)) * 128 + (((chunk & 7) ^ rr) << 4);
#pragma unroll
    for (int hh = 0; hh < 2; hh++) {
        mbar_wait(bar + hh * 8, 0);
#pragma unroll
        for (int k = 0; k < 4; k++) ldsm4t(a[hh * 4 + k], a0 + hh * CH + k * 2048);
    }
}
__device__ __forceinline__ void matvec_mma(float (&c)[4], const uint32_t (&a)[8][4], uint32_t vec, int nvec, int lane) {
    const uint32_t va = vec + (lane & (nvec - 1)) * VROW + (lane >> 3) * 16;
    float d[4][4];
#pragma unroll
    for (int q = 0; q < 4; q++) {
        uint32_t b[4];
        ldsm4(b, va + q * 64);
        d[q][0] = d[q][1] = d[q][2] = d[q][3] = 0.f;
        mma(d[q], a[2 * q], b[0], b[1]);
        mma(d[q], a[2 * q + 1], b[2], b[3]);
    }
#pragma unroll
    for (int k = 0; k < 4; k++) c[k] = (d[0][k] + d[1][k]) + (d[2][k] + d[3][k]);
}
__device__ __forceinline__ void matvecT(float (&c)[4], uint32_t tile, uint32_t vec, int nvec, uint32_t bar, int w, int lane) {
    uint32_t a[8][4];
    matvec_loadA(a, tile, bar, w, lane);
    matvec_mma(c, a, vec, nvec, lane);
}
template <class T> __device__ __forceinline__ T* pin(T* p) { asm volatile("" : "+l"(p)); return p; }
__device__ __forceinline__ void post(uint32_t* p, float v) {
    asm volatile("red.relaxed.gpu.global.add.u32 [%0], %1;" ::"l"(p), "r"(~__float_as_uint(v)) : "memory");
}
__device__ __forceinline__ void ld4_if(const void* p, uint4& x, bool need) {
    asm volatile("{\n.reg .pred q;\nsetp.ne.u32 q, %5, 0;\n@q ld.relaxed.gpu.global.v4.b32 {%0,%1,%2,%3}, [%4];\n}"
                 : "+r"(x.x), "+r"(x.y), "+r"(x.z), "+r"(x.w) : "l"(p), "r"((uint32_t)need) : "memory");
}
__device__ __forceinline__ void merge_store(const uint4 (&x)[5], uint32_t dst) {
#pragma unroll
    for (int b = 0; b < 2; b++) {
        const float l0 = __uint_as_float(~(b ? x[4].z : x[4].x)), l1 = __uint_as_float(~(b ? x[4].w : x[4].y));
        const float mx = fmaxf(l0, l1), e0 = ex2(l0 - mx), e1 = ex2(l1 - mx), r = rcp(e0 + e1);
        const uint4 u = x[2 * b], v = x[2 * b + 1];
        const uint32_t lo = pack2((e0 * __uint_as_float(~u.x) + e1 * __uint_as_float(~v.x)) * r, (e0 * __uint_as_float(~u.y) + e1 * __uint_as_float(~v.y)) * r);
        const uint32_t hi = pack2((e0 * __uint_as_float(~u.z) + e1 * __uint_as_float(~v.z)) * r, (e0 * __uint_as_float(~u.w) + e1 * __uint_as_float(~v.w)) * r);
        asm volatile("st.shared.v2.b32 [%0], {%1,%2};" ::"r"(dst + b * YROW), "r"(lo), "r"(hi) : "memory");
    }
}

__global__ void __launch_bounds__(NTHREADS, 1)
fused_decode_kernel(const char* __restrict__ wqraw, Scratch* const sc, const __nv_bfloat16* __restrict__ xA, const __nv_bfloat16* __restrict__ xB,
                    const char* __restrict__ Kc, const char* __restrict__ Vc, const __grid_constant__ Maps maps,
                    const char* __restrict__ woA, const char* __restrict__ woB, __nv_bfloat16* __restrict__ out, const uint32_t zero) {
    unsigned* const cnt = sc->cnt;
    asm volatile("{\n.reg .pred p;\nsetp.eq.u32 p, %1, 0;\n@p cp.async.bulk.prefetch.L2.global [%0], %2;\n}"
                 ::"l"(wqraw + (size_t)blockIdx.x * (2 * CH)), "r"(threadIdx.x), "n"(CH) : "memory");
    extern __shared__ char smem_raw[];
    const uint32_t sm = ((uint32_t)__cvta_generic_to_shared(smem_raw) + 1023u) & ~1023u;
    if (threadIdx.x == 64) {
        unsigned epoch;
        asm volatile("atom.relaxed.gpu.global.add.u32 %0, [%1], 1;" : "=r"(epoch) : "l"(cnt) : "memory");
        sts32(sm + OFF_TAG, (epoch >> 7) + 1u);
    }
    const uint32_t bars = sm + OFF_BAR;
    const int cta = blockIdx.x, h = cta >> 2, j = cta & 3;
    uint64_t pol = 0;
    if (threadIdx.x == 0) {
        TS(0);
        asm volatile("createpolicy.fractional.L2::evict_first.b64 %0, 1.0;" : "=l"(pol));
#pragma unroll
        for (int i = 0; i < WIN; i++) mbar_init(bars + (B_WQB + i) * 8, 1);
        asm volatile("fence.mbarrier_init.release.cluster;" ::: "memory");
#pragma unroll
        for (int i = 0; i < WIN; i++) {
            mbar_expect(bars + (B_WQB + i) * 8, CH);
            tma3d(sm + OFF_S0 + i * CH, &maps.wqB + (i >> 1), j * 128 + (i & 1) * 64, h * 2, bars + (B_WQB + i) * 8, pol);
        }
    }
    const int tid = threadIdx.x < 64 ? threadIdx.x + 384 : threadIdx.x - 64, warp = tid >> 5, lane = tid & 31;

    if (warp == 12) {
        const size_t kvoff = ((size_t)(((j >> 1) * 32 + h) * 4096 + (j & 1) * 2048)) * 256;
        const char* kp = Kc + kvoff;
        const char* vp = Vc + kvoff;
        __syncwarp();
        bar_arrive(0, NTHREADS);
        bar_sync(3, 64);
        if (lane == 0) {
            uint32_t pb[WHI];
#pragma unroll
            for (int i = 0; i < WHI; i++) pb[i] = i < WHI - WIN ? (bars + B_WO * 8) | 1u : bars + (B_WQB + i - (WHI - WIN)) * 8;
            auto pace = [&](uint32_t bar, uint32_t par) {
                uint32_t it = 0;
                while (true) {
                    const uint32_t win = ldsv(sm + OFF_WIN);
                    uint32_t busy = 0;
#pragma unroll
                    for (int i = 0; i < WHI; i++) busy += mbar_test(pb[i] & ~1u, pb[i] & 1u) ^ 1u;
                    if (busy < win) break;
                    if (++it > SPIN_MAX) __trap();
                }
#pragma unroll
                for (int i = 0; i + 1 < WHI; i++) pb[i] = pb[i + 1];
                pb[WHI - 1] = bar | par;
            };
            auto side = [&](const CUtensorMap* m, uint32_t dst, int bidx, int c1, int c2) {
                const uint32_t bar = bars + bidx * 8;
                pace(bar, 0);
                mbar_expect(bar, CH);
                tma3d(dst, m, c1, c2, bar, pol);
            };
#pragma unroll 1
            for (int i = WIN; i < 6; i++)
                side(&maps.wqB + (i >> 1), sm + OFF_S0 + i * CH, B_WQB + i, j * 128 + (i & 1) * 64, h * 2);
            TS(1);
            uint32_t slot = 0, use = 0;
            int nuv = 0;
#pragma unroll 1
            for (int n = 0; n < 2 * NTILE; n++) {
                if (n == RING) {
                    mbar_wait(bars + B_FREE * 8, 0);
#pragma unroll 1
                    for (int q = 0; q < 4; q++) side(&maps.ckv, sm + OFF_S0 + q * CH, B_CKV + q, cta * 64 + q * 16, 0);
                }
                if (nuv < 2 && n > RING && (n >= 2 * NTILE - 8 || mbar_test(bars + B_FREE * 8, 1))) {
                    mbar_wait(bars + B_FREE * 8, 1);
                    side(&maps.wuv, sm + OFF_S1 + nuv * CH, B_WUV + nuv, j * 128 + nuv * 64, h * 2);
                    nuv++;
                }
                const uint32_t fb = bars + slot * 8;
                pace(fb, use & 1);
                mbar_wait(fb + B_EMPTY * 8, (use & 1) ^ 1);
                mbar_expect(fb, CH);
                bulk1d(sm + OFF_RING + slot * CH, ((n & 1) ? vp : kp) + (size_t)(n >> 1) * CH, fb, pol);
                if (n >= FINE_V || (n & 1)) {
                    asm volatile("red.relaxed.gpu.global.add.u32 [%0], %1;" ::"l"(cnt + 3), "r"(n >= FINE_V ? 1 : 2) : "memory");
                    stsv(sm + OFF_NOW, n + 1);
                }
                if (++slot == RING) { slot = 0; use++; }
            }
            TS(2);
            mbar_wait(bars + B_FREE * 8, 0);
            const char* wp = ((cta & 1) ? woB : woA) + (cta >> 1) * 8192;
            uint32_t it = 0;
#pragma unroll 1
            for (int q = 0; q <= 8; q++) {
                const uint32_t bar = bars + (B_WO + q - 1) * 8;
                if (q) mbar_expect(bar, CH / 2);
                while (true) {
                    const uint32_t t0 = ldsv(sm + OFF_TBOX);
                    if (t0 && gtime() - t0 + 16384u >= 16384u + q * BOX_NS) break;
                    if (++it > SPIN_MAX) __trap();
                }
                if (q < 8) asm volatile("cp.async.bulk.prefetch.L2.global.L2::cache_hint [%0], %1, %2;" ::"l"(wp + q * 524288), "n"(CH / 2), "l"(pol) : "memory");
                if (q) tma3d(sm + OFF_S0 + (q - 1) * (CH / 2), &maps.woA + (cta & 1), (q - 1) * 512 + (cta >> 4) * 64, (cta >> 1) & 7, bar, pol);
            }
            TS(3);
        }
    } else if (warp == 13) {
        if (lane == 0) {
#pragma unroll
            for (int i = 0; i < NBAR; i++)
                if (i < B_WQB || i >= B_WQB + WIN)
                    mbar_init(bars + i * 8, i == B_FREE ? 8 : (i >= B_EMPTY && i < B_EMPTY + RING) ? 4 : 1);
            asm volatile("fence.mbarrier_init.release.cluster;" ::: "memory");
#pragma unroll
            for (int i = 2; i < 8; i++) asm volatile("prefetch.tensormap [%0];" ::"l"(&maps.wqB + i) : "memory");
            stsv(sm + OFF_NOW, 0); stsv(sm + OFF_WIN, WIN); stsv(sm + OFF_TBOX, 0);
        }
        __syncwarp();
        bar_arrive(3, 64);
        bar_sync(0, NTHREADS);
        if (lane == 0) {
            const uint32_t base = (lds32(sm + OFF_TAG) - 1u) * (NCTA * 2 * NTILE);
            mbar_wait(bars + (B_WUK + 1) * 8, 0);
            uint32_t it = 0, tbox = 0;
            while (true) {
                const uint32_t n = ldsv(sm + OFF_NOW);
                uint32_t v;
                asm volatile("ld.relaxed.gpu.global.u32 %0, [%1];" : "=r"(v) : "l"(cnt + 3) : "memory");
                v -= base;
                if (v >= NCTA * EST_FROM && (v <= NCTA * EST_TO || !tbox)) {
                    const uint32_t est = (gtime() + (NCTA * 2 * NTILE - v) * BOX_NS / 64 + (uint32_t)(BOX_SHIFT + (~cta & 1) * (BOX_NS / 2))) | 1u;
                    if (!tbox || (int)(est - tbox) < 0) { tbox = est; stsv(sm + OFF_TBOX, est); }
                }
                if (v >= NCTA * 2 * NTILE - GATE_W) break;
                const int diff = (int)(n * NCTA) - (int)v;
                stsv(sm + OFF_WIN, diff < -THETA ? WHI : WIN - (diff > THETA) - (v >= NCTA * END_V));
                if (++it > SPIN_MAX) __trap();
                __nanosleep(v < NCTA * FINE_V ? BACKOFF3 : BACKOFF2);
            }
            stsv(sm + OFF_WIN, WHI);
            TS(24);
        }
    } else if (warp < 4) {
        const int g = lane >> 2, t = lane & 3, i = lane >> 3, rr = lane & 7;
        bar_sync(0, NTHREADS);
        const uint32_t tag = lds32(sm + OFF_TAG);
        {
            mbar_wait(bars + 8, 0);
            float q0, q1;
            ll_gather4(&sc->e1[0][h * 4][tid], tag, q0, q1);
            sts16(sm + OFF_QB + tid * 2, f2bf((j >> 1) ? q1 : q0));
        }
        bar_sync(1, 128);
        if (tid == 0) TS(4);
        uint32_t qf[8][2];
#pragma unroll
        for (int c = 0; c < 8; c++) {
            const uint32_t a = sm + OFF_QB + (((c + g) & 7) * 8 + 2 * t) * 2;
            qf[c][0] = lds32(a); qf[c][1] = lds32(a + 128);
        }
        float acc[8][4];
#pragma unroll
        for (int c = 0; c < 8; c++) { acc[c][0] = acc[c][1] = acc[c][2] = acc[c][3] = 0.f; }
        float m = -INFINITY, l = 0.f;
        const bool diag = (t == (g >> 1));
        const uint32_t krow = sm + OFF_RING + (warp * 16 + rr + 8 * (i & 1)) * 256 + (i >> 1) * 128;
        const uint32_t vrow = sm + OFF_RING + (warp * 16 + rr + 8 * (i >> 1)) * 256 + (i & 1) * 128;
        uint32_t slot = 0, ph = 0;
        uint32_t* const e5own = pin(&sc->e5[cta][tid]);
        uint32_t a[8][4], b0, b1;
#pragma unroll 1
        for (int tile = 0;; tile++) {
            mbar_wait(bars + slot * 8, ph);
#pragma unroll
            for (int c = 0; c < 8; c++) ldsm4(a[c], krow + slot * CH + (((c + rr) & 7) << 4));
            __syncwarp();
            if (lane == 0) mbar_arrive(bars + (B_EMPTY + slot) * 8 + ((a[0][0] | a[1][0] | a[2][0] | a[3][0] | a[4][0] | a[5][0] | a[6][0] | a[7][0]) & zero));
            if (++slot == RING) { slot = 0; ph ^= 1; }
            float s0[4] = {0.f, 0.f, 0.f, 0.f}, s1[4] = {0.f, 0.f, 0.f, 0.f};
#pragma unroll
            for (int c = 0; c < 8; c += 2) { mma(s0, a[c], qf[c][0], qf[c][1]); mma(s1, a[c + 1], qf[c + 1][0], qf[c + 1][1]); }
            float slo = (g & 1) ? s0[1] + s1[1] : s0[0] + s1[0];
            float shi = (g & 1) ? s0[3] + s1[3] : s0[2] + s1[2];
            slo = diag ? bfround(bfround(slo) * SCALE) : -INFINITY;
            shi = diag ? bfround(bfround(shi) * SCALE) : -INFINITY;
            int key = __float_as_int(fmaxf(slo, shi));
            key ^= (key >> 31) & 0x7fffffff;
            key = __reduce_max_sync(0xffffffffu, key);
            key ^= (key >> 31) & 0x7fffffff;
            const float mn = fmaxf(m, __int_as_float(key));
            const float alpha = ex2((m - mn) * LOG2E);
            m = mn;
            const float plo = ex2((slo - mn) * LOG2E), phi = ex2((shi - mn) * LOG2E);
            l = l * alpha + (plo + phi);
            b0 = (g & 1) ? pack2(0.f, plo) : pack2(plo, 0.f);
            b1 = (g & 1) ? pack2(0.f, phi) : pack2(phi, 0.f);
#pragma unroll
            for (int c = 0; c < 8; c++) { acc[c][0] *= alpha; acc[c][1] *= alpha; acc[c][2] *= alpha; acc[c][3] *= alpha; }
            if (tile == NTILE - 1) break;
            mbar_wait(bars + slot * 8, ph);
#pragma unroll
            for (int c = 0; c < 8; c++) ldsm4t(a[c], vrow + slot * CH + (((c + rr) & 7) << 4));
            __syncwarp();
            if (lane == 0) mbar_arrive(bars + (B_EMPTY + slot) * 8 + ((a[0][0] | a[1][0] | a[2][0] | a[3][0] | a[4][0] | a[5][0] | a[6][0] | a[7][0]) & zero));
            if (++slot == RING) { slot = 0; ph ^= 1; }
#pragma unroll
            for (int c = 0; c < 8; c++) mma(acc[c], a[c], b0, b1);
        }
#pragma unroll
        for (int o = 16; o; o >>= 1) l += __shfl_xor_sync(0xffffffffu, l, o);
        if (lane == 0) stsf2(sm + OFF_ML + warp * 8, m, l);
        mbar_wait(bars + B_S2 * 8, 0);
        bar_sync(1, 128);
        {
            const uint4 ml0 = lds128(sm + OFF_ML), ml1 = lds128(sm + OFF_ML + 16);
            const float m0 = __uint_as_float(ml0.x), m1 = __uint_as_float(ml0.z), m2 = __uint_as_float(ml1.x), m3 = __uint_as_float(ml1.z);
            const float M = fmaxf(fmaxf(m0, m1), fmaxf(m2, m3));
            const float L = (ex2((m0 - M) * LOG2E) * __uint_as_float(ml0.y) + ex2((m1 - M) * LOG2E) * __uint_as_float(ml0.w))
                          + (ex2((m2 - M) * LOG2E) * __uint_as_float(ml1.y) + ex2((m3 - M) * LOG2E) * __uint_as_float(ml1.w));
            const float f = ex2((m - M) * LOG2E) * rcp(L);
            if (tid == 0) post(e5own + (NCTA - cta) * 128 + cta, M * LOG2E + lg2(L));
            mbar_wait(bars + slot * 8, ph);
#pragma unroll
            for (int c = 0; c < 8; c++) ldsm4t(a[c], vrow + slot * CH + (((c + rr) & 7) << 4));
#pragma unroll
            for (int c = 0; c < 8; c++) mma(acc[c], a[c], b0, b1);
            if (tid == 0) TS(5);
            float v[2][8];
#pragma unroll
            for (int c = 0; c < 8; c++) { v[0][c] = acc[c][0] + acc[(c + 7) & 7][1]; v[1][c] = acc[c][2] + acc[(c + 7) & 7][3]; }
#pragma unroll
            for (int c = 0; c < 4; c++) { v[0][c] += __shfl_xor_sync(0xffffffffu, v[0][c + 4], 2); v[1][c] += __shfl_xor_sync(0xffffffffu, v[1][c + 4], 2); }
            const int src = (lane & ~3) | ((lane + 3) & 3);
#pragma unroll
            for (int c = 0; c < 2; c++) { v[0][c] += __shfl_sync(0xffffffffu, v[0][c + 2], src); v[1][c] += __shfl_sync(0xffffffffu, v[1][c + 2], src); }
            const uint32_t wa = sm + OFF_S2 + (warp * 160 + 16 * t + 8 * (t >> 1) + g) * 4;
            sts32(wa, __float_as_uint(v[0][0] * f)); sts32(wa + 32, __float_as_uint(v[0][1] * f));
            sts32(wa + 320, __float_as_uint(v[1][0] * f)); sts32(wa + 352, __float_as_uint(v[1][1] * f));
            bar_sync(1, 128);
            const uint32_t ra = sm + OFF_S2 + (tid + warp * 8) * 4;
            post(e5own, (ldsf(ra) + ldsf(ra + 640)) + (ldsf(ra + 1280) + ldsf(ra + 1920)));
        }
        if (tid == 0) TS(6);
        if (cta & 1) {
            const int c0 = (tid >> 4) * 16 + (cta >> 5) * 4;
            const uint32_t* p = e5own + ((c0 - cta) * 128 + (cta >> 4 & 1) * 64 + (lane & 15) * 4 - tid);
            const uint32_t* pl = e5own + ((NCTA - cta) * 128 + c0 - tid);
            uint4 x[5];
            bool need[5] = {true, true, true, true, true};
            uint32_t it = 0;
            while (true) {
#pragma unroll
                for (int q = 0; q < 5; q++) ld4_if(q < 4 ? p + q * 128 : pl, x[q], need[q]);
#pragma unroll
                for (int q = 0; q < 5; q++) need[q] = !x[q].x || !x[q].y || !x[q].z || !x[q].w;
                if (!__any_sync(0xffffffffu, need[0] | need[1] | need[2] | need[3] | need[4])) break;
                if (++it > SPIN_MAX) __trap();
            }
            merge_store(x, sm + OFF_Y + warp * YHEAD + lane * 8);
            bar_arrive(4, 256 + 128);
        }
        if (tid == 0) TS(16);
    } else {
        const int st = tid - 128, w = warp - 4;
        const int g = lane >> 2, t = lane & 3, i = lane >> 3, rr = lane & 7;
        if (st < 64) {
            const int which = st >> 5, b = (st >> 4) & 1, c = st & 15;
            const uint4 v = __ldg((const uint4*)((which ? xA : xB) + b * 512 + j * 128) + c);
            sts128(sm + OFF_XB + (which * 2 + b) * VROW + c * 16, v);
        }
        bar_sync(0, NTHREADS);
        const uint32_t tag = lds32(sm + OFF_TAG);
        float c[4];
#pragma unroll 1
        for (int which = 0; which < 2; which++) {
            matvecT(c, sm + OFF_S0 + which * 2 * CH, sm + OFF_XB + which * 2 * VROW, 2, bars + (B_WQB + which * 2) * 8, w, lane);
            if (t == 0) {
                ll_store2(&sc->e1[which][cta][w * 16 + g], c[0], c[1], tag);
                ll_store2(&sc->e1[which][cta][w * 16 + g + 8], c[2], c[3], tag);
            }
        }
        __syncwarp();
        if (lane == 0) mbar_arrive(bars + B_FREE * 8);
        if (st == 0) TS(8);
        if (st < 128) {
            float q0, q1;
            sleep_ns(POLL_DELAY);
            ll_gather4(&sc->e1[1][h * 4][st], tag, q0, q1);
            sts16(sm + OFF_QA + st * 2, f2bf(q0)); sts16(sm + OFF_QA + VROW + st * 2, f2bf(q1));
        }
        bar_sync(2, 256);
        if (st == 0) TS(9);
        {
            const int row = w * 16 + rr + 8 * (i & 1);
            const uint32_t a0 = sm + OFF_S2 + (row >> 6) * CH + (row & 63) * 128;
            const uint32_t va = sm + OFF_QA + g * VROW + t * 4;
            float d[4] = {0.f, 0.f, 0.f, 0.f};
            c[0] = c[1] = c[2] = c[3] = 0.f;
            mbar_wait(bars + (B_WUK + (w >> 2)) * 8, 0);
#pragma unroll
            for (int ks = 0; ks < 8; ks++) {
                const int chunk = 2 * ks + (i >> 1);
                uint32_t a[4];
                ldsm4(a, a0 + (chunk >> 3) * 8192 + (((chunk & 7) ^ rr) << 4));
                const uint32_t b0 = (g < 2) ? lds32(va + ks * 32) : 0u, b1 = (g < 2) ? lds32(va + ks * 32 + 16) : 0u;
                if (ks & 1) mma(d, a, b0, b1); else mma(c, a, b0, b1);
            }
            if (t == 0) {
                const uint32_t qs = sm + OFF_QS + (w * 16 + g) * 2;
                sts16(qs, f2bf(c[0] + d[0])); sts16(qs + VROW, f2bf(c[1] + d[1]));
                sts16(qs + 16, f2bf(c[2] + d[2])); sts16(qs + VROW + 16, f2bf(c[3] + d[3]));
            }
            bar_sync(2, 256);
            if (w == 0) {
                const int b = lane >> 4, cc = lane & 15;
                sc->qabs[(b * 32 + h) * 64 + ((j * 16 + cc) ^ (h & 7))] = lds128(sm + OFF_QS + b * VROW + cc * 16);
                __syncwarp();
                if (lane == 0) {
                    cnt_rendezvous(cnt + 1, tag * 128u, 18);
                    TS(10);
                    mbar_expect(bars + B_GATH * 8, 2 * CH);
                    bulk1d_n(sm + OFF_S2, sc->qabs + (cta >> 6) * 2048, 2 * CH, bars + B_GATH * 8);
                }
                __syncwarp();
            }
        }
        mbar_wait(bars + B_GATH * 8, 0);
        if (st == 0) TS(11);
        {
            const int mt = w & 1, kg = w >> 1;
            const uint32_t qa = sm + OFF_S2 + (mt * 16 + rr + 8 * (i & 1)) * 1024;
            const uint32_t ka = sm + OFF_S0 + kg * CH + (rr + 8 * (i >> 1)) * 128;
            float s0[4] = {0.f, 0.f, 0.f, 0.f}, s1[4] = {0.f, 0.f, 0.f, 0.f};
            mbar_wait(bars + (B_CKV + kg) * 8, 0);
#pragma unroll 2
            for (int gq = 0; gq < 8; gq++) {
#pragma unroll
                for (int k4 = 0; k4 < 4; k4++) {
                    uint32_t a[4], b[4];
                    ldsm4(a, qa + gq * 128 + (((2 * k4 + (i >> 1)) ^ rr) << 4));
                    ldsm4(b, ka + gq * 2048 + (((2 * k4 + (i & 1)) ^ rr) << 4));
                    mma(s0, a, b[0], b[1]);
                    mma(s1, a, b[2], b[3]);
                }
            }
            const uint32_t sa = sm + OFF_SC + ((mt * 16 + g) * 68 + kg * 16 + 2 * t) * 4;
            stsf2(sa, s0[0], s0[1]); stsf2(sa + 32, s1[0], s1[1]);
            stsf2(sa + 8 * 68 * 4, s0[2], s0[3]); stsf2(sa + 8 * 68 * 4 + 32, s1[2], s1[3]);
        }
        bar_sync(2, 256);
        {
            const int head = w * 4 + i;
            const uint32_t sa = sm + OFF_SC + (head * 68 + rr * 8) * 4;
            const uint4 u0 = lds128(sa), u1 = lds128(sa + 16);
            float s[8] = {__uint_as_float(u0.x), __uint_as_float(u0.y), __uint_as_float(u0.z), __uint_as_float(u0.w),
                          __uint_as_float(u1.x), __uint_as_float(u1.y), __uint_as_float(u1.z), __uint_as_float(u1.w)};
            float mx = s[0];
#pragma unroll
            for (int k = 1; k < 8; k++) mx = fmaxf(mx, s[k]);
#pragma unroll
            for (int o = 1; o < 8; o <<= 1) mx = fmaxf(mx, __shfl_xor_sync(0xffffffffu, mx, o));
            float sum = 0.f;
#pragma unroll
            for (int k = 0; k < 8; k++) { s[k] = ex2((s[k] - mx) * (SCALE * LOG2E)); sum += s[k]; }
#pragma unroll
            for (int o = 1; o < 8; o <<= 1) sum += __shfl_xor_sync(0xffffffffu, sum, o);
            const float inv = __fdividef(1.f, sum);
            uint4 p;
            p.x = pack2(s[0] * inv, s[1] * inv); p.y = pack2(s[2] * inv, s[3] * inv);
            p.z = pack2(s[4] * inv, s[5] * inv); p.w = pack2(s[6] * inv, s[7] * inv);
            sts128(sm + OFF_P + head * 128 + ((rr ^ (head & 7)) << 4), p);
            if (rr == 0) ((float*)sc->lse)[head * 128 + cta] = mx * (SCALE * LOG2E) + lg2(sum);
        }
        bar_sync(2, 256);
        {
            float o[2][8][4];
#pragma unroll
            for (int mt = 0; mt < 2; mt++)
#pragma unroll
                for (int n = 0; n < 8; n++) { o[mt][n][0] = o[mt][n][1] = o[mt][n][2] = o[mt][n][3] = 0.f; }
            const uint32_t pa = sm + OFF_P + (rr + 8 * (i & 1)) * 128;
            const uint32_t va = sm + OFF_S0 + w * 2048 + (rr + 8 * (i & 1)) * 128;
#pragma unroll 1
            for (int kq = 0; kq < 4; kq++) {
                uint32_t a0[4], a1[4];
                ldsm4(a0, pa + (((2 * kq + (i >> 1)) ^ rr) << 4));
                ldsm4(a1, pa + 2048 + (((2 * kq + (i >> 1)) ^ rr) << 4));
#pragma unroll
                for (int n = 0; n < 8; n += 2) {
                    uint32_t b[4];
                    ldsm4t(b, va + kq * CH + (((n + (i >> 1)) ^ rr) << 4));
                    mma(o[0][n], a0, b[0], b[1]); mma(o[1][n], a1, b[0], b[1]);
                    mma(o[0][n + 1], a0, b[2], b[3]); mma(o[1][n + 1], a1, b[2], b[3]);
                }
            }
#pragma unroll
            for (int mt = 0; mt < 2; mt++)
#pragma unroll
                for (int hf = 0; hf < 2; hf++) {
                    const uint32_t dst = sm + OFF_S2 + (mt * 16 + hf * 8 + g) * 1024 + w * 128 + t * 16;
#pragma unroll
                    for (int nb = 0; nb < 2; nb++) {
                        uint4 v;
                        v.x = pack2(o[mt][nb * 4 + 0][hf * 2], o[mt][nb * 4 + 0][hf * 2 + 1]);
                        v.y = pack2(o[mt][nb * 4 + 1][hf * 2], o[mt][nb * 4 + 1][hf * 2 + 1]);
                        v.z = pack2(o[mt][nb * 4 + 2][hf * 2], o[mt][nb * 4 + 2][hf * 2 + 1]);
                        v.w = pack2(o[mt][nb * 4 + 3][hf * 2], o[mt][nb * 4 + 3][hf * 2 + 1]);
                        sts128(dst + nb * 64, v);
                    }
                }
            asm volatile("fence.proxy.async.shared::cta;" ::: "memory");
            __syncwarp();
            if (lane == 0) mbar_arrive(bars + B_FREE * 8);
            sc->e4[cta][st] = 0u;
            if (st < 128) sc->e5[cta][st] = 0u;
            else if (cta == 0) sc->e5[NCTA][st - 128] = 0u;
            if (st >= 248) ((uint32_t*)out)[cta * 8 + st - 248] = 0u;
        }
        bar_sync(2, 256);
        if (st == 0) {
            TS(12);
#pragma unroll 1
            for (int k = 0; k < ST_SPLIT; k++) {
                asm volatile("cp.async.bulk.tensor.3d.global.shared::cta.bulk_group [%0, {%2,%3,%4}], [%1];"
                             ::"l"(&maps.ctxp), "r"(sm + OFF_S2 + k * (2 * CH / ST_SPLIT)), "r"(0), "r"(cta), "r"(k * (128 / ST_SPLIT)) : "memory");
                if (k + 1 < ST_SPLIT) __nanosleep(ST_GAP);
            }
            asm volatile("cp.async.bulk.commit_group;" ::: "memory");
            asm volatile("cp.async.bulk.wait_group 0;" ::: "memory");
            cnt_rendezvous(cnt + 2, tag * 128u, 20);
            TS(13);
            mbar_expect(bars + B_GATH * 8, 2 * CH + 512);
            bulk1d_n(sm + OFF_LSE, sc->lse + h * 32, 512, bars + B_GATH * 8);
#pragma unroll 1
            for (int k = 0; k < ST_SPLIT; k++) {
                bulk1d_n(sm + OFF_S2 + k * (2 * CH / ST_SPLIT), sc->ctxp + cta * 2048 + k * (2048 / ST_SPLIT), 2 * CH / ST_SPLIT, bars + B_GATH * 8);
                __nanosleep(LD_GAP);
            }
        }
        __syncwarp();
        {
            mbar_wait(bars + B_GATH * 8, 1);
            if (st == 0) TS(22);
            uint4 v[8];
#pragma unroll
            for (int k = 0; k < 8; k++) v[k] = lds128(sm + OFF_S2 + (k * 256 + st) * 16);
            float ls[4];
#pragma unroll
            for (int k = 0; k < 4; k++) ls[k] = ldsf(sm + OFF_LSE + (k * 32 + lane) * 4);
            float m0 = fmaxf(ls[0], ls[1]), m1 = fmaxf(ls[2], ls[3]);
#pragma unroll
            for (int o = 16; o; o >>= 1) { m0 = fmaxf(m0, __shfl_xor_sync(0xffffffffu, m0, o)); m1 = fmaxf(m1, __shfl_xor_sync(0xffffffffu, m1, o)); }
            ls[0] = ex2(ls[0] - m0); ls[1] = ex2(ls[1] - m0); ls[2] = ex2(ls[2] - m1); ls[3] = ex2(ls[3] - m1);
            float z0 = ls[0] + ls[1], z1 = ls[2] + ls[3];
#pragma unroll
            for (int o = 16; o; o >>= 1) { z0 += __shfl_xor_sync(0xffffffffu, z0, o); z1 += __shfl_xor_sync(0xffffffffu, z1, o); }
            z0 = __fdividef(1.f, z0); z1 = __fdividef(1.f, z1);
            ls[0] *= z0; ls[1] *= z0; ls[2] *= z1; ls[3] *= z1;
            float a[2][8];
#pragma unroll
            for (int e = 0; e < 8; e++) a[0][e] = a[1][e] = 0.f;
            const int rg = st >> 4;
#pragma unroll
            for (int k = 0; k < 8; k++) {
                const float wt = __shfl_sync(0xffffffffu, ls[k >> 1], rg + 16 * (k & 1));
                const uint32_t u[4] = {v[k].x, v[k].y, v[k].z, v[k].w};
#pragma unroll
                for (int e = 0; e < 4; e++) {
                    a[k >> 2][2 * e] += wt * __uint_as_float(u[e] << 16);
                    a[k >> 2][2 * e + 1] += wt * __uint_as_float(u[e] & 0xffff0000u);
                }
            }
            const int b = lane >> 4, u16 = lane & 15;
            const uint32_t ra = sm + OFF_SC + (w * 256 + b * 128 + (u16 >> 3) * 64 + ((u16 >> 2) & 1) * 32 + (u16 & 3) * 2) * 4;
#pragma unroll
            for (int e = 0; e < 8; e += 2) {
                const float k0 = b ? a[1][e] : a[0][e], k1 = b ? a[1][e + 1] : a[0][e + 1];
                const float s0 = b ? a[0][e] : a[1][e], s1 = b ? a[0][e + 1] : a[1][e + 1];
                stsf2(ra + (e >> 1) * 32, k0 + __shfl_xor_sync(0xffffffffu, s0, 16), k1 + __shfl_xor_sync(0xffffffffu, s1, 16));
            }
            bar_sync(2, 256);
            if (st == 0) mbar_arrive(bars + B_S2 * 8);
            float s = 0.f;
#pragma unroll
            for (int k = 0; k < 8; k++) s += ldsf(sm + OFF_SC + (k * 256 + st) * 4);
            const float hi = bfround(s);
            const uint32_t ca = sm + OFF_CC + (st >> 7) * VROW + (st & 127) * 2;
            sts16(ca, f2bf(hi)); sts16(ca + 2 * VROW, f2bf(s - hi));
            bar_sync(2, 256);
        }
        matvecT(c, sm + OFF_S1, sm + OFF_CC, 4, bars + B_WUV * 8, w, lane);
#pragma unroll
        for (int k = 0; k < 4; k++) c[k] += __shfl_xor_sync(0xffffffffu, c[k], 1);
        post(&sc->e4[cta][(t & 1) * 128 + w * 16 + (t >> 1) * 8 + g], t == 0 ? c[0] : t == 1 ? c[1] : t == 2 ? c[2] : c[3]);
        __syncwarp();
        if (lane == 0) mbar_arrive(bars + B_FREE * 8);
        if (st == 0) TS(23);
        if (st < 128) sts32(sm + OFF_PAIR + st * 4, EMPTY);
        if (!(cta & 1)) {
            const uint32_t* p = &sc->e4[((w & 6) + (lane >> 4)) * 16 + (cta >> 5) * 4][(w & 1) * 128 + (cta >> 4 & 1) * 64 + (lane & 15) * 4];
            uint4 x[4];
            bool need[4] = {true, true, true, true};
            uint32_t it = 0;
            sleep_ns(POLL_DELAY2);
            while (true) {
#pragma unroll
                for (int q = 0; q < 4; q++) ld4_if(p + q * 256, x[q], need[q]);
#pragma unroll
                for (int q = 0; q < 4; q++) need[q] = !x[q].x || !x[q].y || !x[q].z || !x[q].w;
                if (!__any_sync(0xffffffffu, need[0] | need[1] | need[2] | need[3])) break;
                if (++it > SPIN_MAX) __trap();
                __nanosleep(BACKOFF);
            }
            auto sum4 = [](uint32_t a, uint32_t b, uint32_t c, uint32_t d) {
                return (__uint_as_float(~a) + __uint_as_float(~b)) + (__uint_as_float(~c) + __uint_as_float(~d));
            };
            asm volatile("st.shared.v2.b32 [%0], {%1,%2};" ::"r"(sm + OFF_Y + (w & 1) * YROW + (w >> 1) * YHEAD + lane * 8),
                         "r"(pack2(sum4(x[0].x, x[1].x, x[2].x, x[3].x), sum4(x[0].y, x[1].y, x[2].y, x[3].y))),
                         "r"(pack2(sum4(x[0].z, x[1].z, x[2].z, x[3].z), sum4(x[0].w, x[1].w, x[2].w, x[3].w))) : "memory");
        }
        if (st == 0) TS(14);
        bar_sync(2, 256);
        {
            const int hf = w >> 2, cg = w & 3;
            const uint32_t a0 = sm + OFF_S0 + hf * 8192 + (rr + 8 * (i >> 1)) * 128 + (((2 * cg + (i & 1)) ^ rr) << 4);
            const uint32_t va = sm + OFF_Y + (lane >> 1 & 1) * YROW + (lane & 1) * YHEAD + hf * 128 + i * 16;
            const uint32_t wb = bars + (B_WO + hf) * 8;
            const uint32_t pa = sm + OFF_PAIR + (cg * 32 + lane) * 4;
            const int col = (t & 1) * 1024 + (cta & 1) * 512 + (cta >> 1 & 7) * 64 + cg * 16 + (t >> 1) * 8 + g;
            __nv_bfloat16* const outp = pin(out + (col & ~1));
            const bool up = t >= 2, odd = g & 1;
            uint32_t a[4][4][4], b[4][4];
            float d[2][4][4];
#pragma unroll
            for (int k = 0; k < 8; k++) d[k >> 2][k & 3][0] = d[k >> 2][k & 3][1] = d[k >> 2][k & 3][2] = d[k >> 2][k & 3][3] = 0.f;
            auto load_w = [&](int hd) {
                mbar_wait(wb + hd * 16, 0);
#pragma unroll
                for (int k = 0; k < 4; k++) ldsm4t(a[hd][k], a0 + hd * CH + k * 2048);
            };
            auto load_y = [&]() {
#pragma unroll
                for (int q = 0; q < 4; q++) ldsm4(b[q], va + (q >> 1) * 2 * YHEAD + (q & 1) * 64);
            };
            auto head = [&](int hd) {
#pragma unroll
                for (int k = 0; k < 4; k++) mma(d[hd & 1][k], a[hd][k], b[(hd & 2) + (k >> 1)][(k & 1) * 2], b[(hd & 2) + (k >> 1)][(k & 1) * 2 + 1]);
            };
            if (cta & 1) {
                load_w(0); load_w(1);
                bar_sync(4, 256 + 128);
                load_y();
                head(0); head(1);
            } else {
                load_y();
                load_w(0); head(0);
                load_w(1); head(1);
            }
            if (st == 0) TS(25);
            load_w(2); head(2);
            float z = up ? (d[0][0][2] + d[0][1][2]) + (d[0][2][2] + d[0][3][2]) : (d[0][0][0] + d[0][1][0]) + (d[0][2][0] + d[0][3][0]);
            mbar_wait_uni(wb + 48);
            if (st == 0) TS(26);
            uint32_t other = ldsv(pa);
#pragma unroll
            for (int k = 0; k < 4; k++) ldsm4t(a[3][k], a0 + 3 * CH + k * 2048);
            head(3);
            z += other != EMPTY ? __uint_as_float(other) : 0.f;
            float z1 = z, z3 = z;
#pragma unroll
            for (int k = 0; k < 3; k++) { z1 += d[1][k][1]; z3 += d[1][k][3]; }
            z = up ? z3 + d[1][3][3] : z1 + d[1][3][1];
            if (st == 0) TS(17);
            asm volatile("{\n.reg .pred p;\nsetp.eq.u32 p, %2, %3;\n@p bra FIRST;\nred.relaxed.gpu.global.add.noftz.bf16x2 [%0], %1;\nexit;\nFIRST:\n}"
                         ::"l"(outp), "r"(odd ? pack2(0.f, z) : pack2(z, 0.f)), "r"(other), "n"(EMPTY) : "memory");
            asm volatile("atom.shared.exch.b32 %0, [%1], %2;" : "=r"(other) : "r"(pa), "r"(__float_as_uint(z)) : "memory");
            z += __uint_as_float(other);
            asm volatile("{\n.reg .pred p;\nsetp.eq.u32 p, %2, %3;\n@p exit;\nred.relaxed.gpu.global.add.noftz.bf16x2 [%0], %1;\n}"
                         ::"l"(outp), "r"(odd ? pack2(0.f, z) : pack2(z, 0.f)), "r"(other), "n"(EMPTY) : "memory");
        }
    }
}

typedef CUresult (*EncodeFn)(CUtensorMap*, CUtensorMapDataType, cuuint32_t, void*, const cuuint64_t*, const cuuint64_t*,
                             const cuuint32_t*, const cuuint32_t*, CUtensorMapInterleave, CUtensorMapSwizzle,
                             CUtensorMapL2promotion, CUtensorMapFloatOOBfill);

void make_map(EncodeFn enc, CUtensorMap* m, void* p, unsigned rows, unsigned cols, unsigned br, unsigned bg) {
    cuuint64_t gd[3] = {64, rows, cols / 64};
    cuuint64_t gs[2] = {(cuuint64_t)cols * 2, 128};
    cuuint32_t bx[3] = {64, br, bg};
    cuuint32_t es[3] = {1, 1, 1};
    enc(m, CU_TENSOR_MAP_DATA_TYPE_BFLOAT16, 3, p, gd, gs, bx, es, CU_TENSOR_MAP_INTERLEAVE_NONE,
        CU_TENSOR_MAP_SWIZZLE_128B, CU_TENSOR_MAP_L2_PROMOTION_L2_128B, CU_TENSOR_MAP_FLOAT_OOB_FILL_NONE);
}

}

extern "C" void kernel_launch(void* const* d_in, const int* in_sizes, int n_in, void* d_out, int out_size) {
    static EncodeFn enc = nullptr;
    if (!enc) {
        void* fn = nullptr;
        cudaDriverEntryPointQueryResult qr;
        cudaGetDriverEntryPoint("cuTensorMapEncodeTiled", &fn, cudaEnableDefault, &qr);
        enc = (EncodeFn)fn;
        cudaFuncSetAttribute(fused_decode_kernel, cudaFuncAttributeMaxDynamicSharedMemorySize, SMEM_BYTES);
    }
    Scratch* sc = nullptr;
    cudaGetSymbolAddress((void**)&sc, g_scratch);
    Maps maps;
    make_map(enc, &maps.wqB, d_in[9], 512, 4096, 64, 2);
    make_map(enc, &maps.wqA, d_in[2], 512, 4096, 64, 2);
    make_map(enc, &maps.wuk, d_in[3], 512, 4096, 64, 2);
    make_map(enc, &maps.wuv, d_in[4], 512, 4096, 64, 2);
    make_map(enc, &maps.woA, d_in[5], 4096, 512, 64, 1);
    make_map(enc, &maps.woB, d_in[10], 4096, 512, 64, 1);
    make_map(enc, &maps.ckv, d_in[1], 8192, 512, 16, 8);
    {
        void* p = sc->ctxp;
        cuuint64_t gd[3] = {128, 128, 128};
        cuuint64_t gs[2] = {256, 32768};
        cuuint32_t bx[3] = {128, 1, 128 / ST_SPLIT};
        cuuint32_t es[3] = {1, 1, 1};
        enc(&maps.ctxp, CU_TENSOR_MAP_DATA_TYPE_BFLOAT16, 3, p, gd, gs, bx, es, CU_TENSOR_MAP_INTERLEAVE_NONE,
            CU_TENSOR_MAP_SWIZZLE_NONE, CU_TENSOR_MAP_L2_PROMOTION_NONE, CU_TENSOR_MAP_FLOAT_OOB_FILL_NONE);
    }
    fused_decode_kernel<<<NCTA, NTHREADS, SMEM_BYTES>>>((const char*)d_in[9], sc, (const __nv_bfloat16*)d_in[0], (const __nv_bfloat16*)d_in[6],
                                                         (const char*)d_in[7], (const char*)d_in[8], maps, (const char*)d_in[5], (const char*)d_in[10],
                                                         (__nv_bfloat16*)d_out, 0u);
}
```

```cpp
#include <cuda_runtime.h>
#include <cuda.h>
#include <cuda_bf16.h>
#include <stdint.h>

#define RING 6
#define WIN 4
#define WHI 5
#define THETA 64
#define END_V 40
#define GATE_W 64
#define BOX_NS 319
#define BOX_SHIFT -25
#define EST_FROM 57
#define EST_TO 62
#define POLL_DELAY 3000
#define POLL_DELAY2 2500
#define ST_SPLIT 8
#define ST_GAP 500
#define LD_GAP 300
#define BACKOFF 200
#define BACKOFF_RV 800
#define FINE_V 52
#define BACKOFF2 100
#define BACKOFF3 300

namespace {

constexpr int NCTA = 128;
constexpr int NTHREADS = 448;
constexpr uint32_t CH = 16384;
constexpr int NTILE = 32;

constexpr uint32_t OFF_RING = 0;
constexpr uint32_t OFF_S0 = RING * CH;
constexpr uint32_t OFF_S1 = OFF_S0 + 2 * CH;
constexpr uint32_t OFF_S2 = OFF_S1 + 2 * CH;
constexpr uint32_t OFF_P = OFF_S2 + 2 * CH;
constexpr uint32_t OFF_SC = OFF_P + 4096;
constexpr uint32_t VROW = 272;
constexpr uint32_t OFF_XB = OFF_SC + 8704;
constexpr uint32_t OFF_XA = OFF_XB + 2 * VROW;
constexpr uint32_t OFF_QA = OFF_XA + 2 * VROW;
constexpr uint32_t OFF_QS = OFF_QA + 2 * VROW;
constexpr uint32_t OFF_CC = OFF_QS + 2 * VROW;
constexpr uint32_t OFF_QB = OFF_CC + 4 * VROW;
constexpr uint32_t OFF_RED = OFF_QB + 1024;
constexpr uint32_t YHEAD = 288, YROW = 4 * YHEAD + 16;
constexpr uint32_t OFF_Y = OFF_RED + 2560;
constexpr uint32_t OFF_PAIR = OFF_Y + 2 * YROW;
constexpr uint32_t EMPTY = 0xffffffffu;
constexpr uint32_t OFF_LSE = OFF_PAIR + 512;
constexpr uint32_t OFF_ML = OFF_LSE + 512;
constexpr uint32_t OFF_TAG = OFF_ML + 32;
constexpr uint32_t OFF_NOW = OFF_TAG + 4;
constexpr uint32_t OFF_WIN = OFF_TAG + 8;
constexpr uint32_t OFF_TBOX = OFF_TAG + 12;
constexpr uint32_t OFF_BAR = OFF_TAG + 16;
constexpr int B_EMPTY = RING;
constexpr int B_WQB = 2 * RING;
constexpr int B_WQA = B_WQB + 2;
constexpr int B_WUK = B_WQA + 2;
constexpr int B_WUV = B_WUK + 2;
constexpr int B_CKV = B_WUV + 2;
constexpr int B_WO = B_CKV + 4;
constexpr int B_FREE = B_WO + 8;
constexpr int B_GATH = B_FREE + 1;
constexpr int B_RV = B_GATH + 1;
constexpr int NBAR = B_RV + 1;
constexpr uint32_t TS_OFF = OFF_BAR + NBAR * 8;
constexpr uint32_t SMEM_USED = TS_OFF;
constexpr uint32_t SMEM_BYTES = SMEM_USED + 1024;
static_assert(SMEM_BYTES <= 232448, "smem");
static_assert(RING >= WHI && WHI >= WIN && WIN >= 3 && WIN <= 6 && FINE_V % 2 == 0, "windows");

constexpr float LOG2E = 1.4426950408889634f;
constexpr float SCALE = 0.08838834764831845f;
#define SPIN_LOG 22
constexpr uint32_t SPIN_MAX = 1u << SPIN_LOG;

struct Maps { CUtensorMap wqB, wqA, wuk, wuv, woA, woB, ckv, ctxp; };

struct Scratch {
    unsigned cnt[64];
    ulonglong2 e1[2][NCTA][128];
    uint4 qabs[2 * 32 * 64];
    float4 lse[32 * 32];
    uint32_t e4[NCTA][256];
    uint32_t e5[4 * NCTA + 4][128];
    uint4 ctxp[NCTA * 128 * 16];
};
__device__ __align__(256) Scratch g_scratch;

#define TS(k) do {} while (0)

__device__ __forceinline__ void mbar_init(uint32_t b, int c) { asm volatile("mbarrier.init.shared::cta.b64 [%0], %1;" ::"r"(b), "r"(c) : "memory"); }
__device__ __forceinline__ void mbar_expect(uint32_t b, uint32_t bytes) { asm volatile("mbarrier.arrive.expect_tx.shared::cta.b64 _, [%0], %1;" ::"r"(b), "r"(bytes) : "memory"); }
__device__ __forceinline__ void mbar_arrive(uint32_t b) { asm volatile("mbarrier.arrive.shared::cta.b64 _, [%0];" ::"r"(b) : "memory"); }
__device__ __forceinline__ void mbar_wait(uint32_t b, uint32_t ph) {
    uint32_t ok, it = 0;
    do {
        asm volatile("{\n.reg .pred p;\nmbarrier.try_wait.parity.shared::cta.b64 p, [%1], %2;\nselp.u32 %0, 1, 0, p;\n}" : "=r"(ok) : "r"(b), "r"(ph) : "memory");
        if (++it > SPIN_MAX) __trap();
    } while (!ok);
}
__device__ __forceinline__ void mbar_wait_uni(uint32_t b) {
    asm volatile("{\n.reg .pred p, q;\n.reg .u32 n;\nmov.u32 n, 0;\nAGAIN:\nadd.u32 n, n, 1;\nsetp.gt.u32 q, n, %1;\n"
                 "mbarrier.try_wait.parity.shared::cta.b64 p, [%0], 0;\n@q trap;\n@!p bra.uni AGAIN;\n}" ::"r"(b), "n"(SPIN_MAX) : "memory");
}
__device__ __forceinline__ uint32_t mbar_test(uint32_t b, uint32_t ph) {
    uint32_t ok;
    asm volatile("{\n.reg .pred p;\nmbarrier.test_wait.parity.shared::cta.b64 p, [%1], %2;\nselp.u32 %0, 1, 0, p;\n}" : "=r"(ok) : "r"(b), "r"(ph) : "memory");
    return ok;
}
__device__ __forceinline__ void bulk1d(uint32_t dst, const void* src, uint32_t bar, uint64_t pol) {
    asm volatile("cp.async.bulk.shared::cluster.global.mbarrier::complete_tx::bytes.L2::cache_hint [%0], [%1], %2, [%3], %4;"
                 ::"r"(dst), "l"(src), "n"(CH), "r"(bar), "l"(pol) : "memory");
}
__device__ __forceinline__ void bulk1d_n(uint32_t dst, const void* src, uint32_t bytes, uint32_t bar) {
    asm volatile("cp.async.bulk.shared::cluster.global.mbarrier::complete_tx::bytes [%0], [%1], %2, [%3];"
                 ::"r"(dst), "l"(src), "r"(bytes), "r"(bar) : "memory");
}
__device__ __forceinline__ void tma3d(uint32_t dst, const CUtensorMap* map, int c1, int c2, uint32_t bar, uint64_t pol) {
    asm volatile("cp.async.bulk.tensor.3d.shared::cluster.global.mbarrier::complete_tx::bytes.L2::cache_hint [%0], [%1, {%3,%4,%5}], [%2], %6;"
                 ::"r"(dst), "l"(map), "r"(bar), "r"(0), "r"(c1), "r"(c2), "l"(pol) : "memory");
}
__device__ __forceinline__ void bar_sync(int id, int n) { asm volatile("barrier.cta.sync %0, %1;" ::"r"(id), "r"(n) : "memory"); }
__device__ __forceinline__ void bar_arrive(int id, int n) { asm volatile("barrier.cta.arrive %0, %1;" ::"r"(id), "r"(n) : "memory"); }
__device__ __forceinline__ void ldsm4(uint32_t (&r)[4], uint32_t a) {
    asm volatile("ldmatrix.sync.aligned.m8n8.x4.shared.b16 {%0,%1,%2,%3}, [%4];" : "=r"(r[0]), "=r"(r[1]), "=r"(r[2]), "=r"(r[3]) : "r"(a) : "memory");
}
__device__ __forceinline__ void ldsm4t(uint32_t (&r)[4], uint32_t a) {
    asm volatile("ldmatrix.sync.aligned.m8n8.x4.trans.shared.b16 {%0,%1,%2,%3}, [%4];" : "=r"(r[0]), "=r"(r[1]), "=r"(r[2]), "=r"(r[3]) : "r"(a) : "memory");
}
__device__ __forceinline__ void mma(float (&c)[4], const uint32_t (&a)[4], uint32_t b0, uint32_t b1) {
    asm volatile("mma.sync.aligned.m16n8k16.row.col.f32.bf16.bf16.f32 {%0,%1,%2,%3}, {%4,%5,%6,%7}, {%8,%9}, {%0,%1,%2,%3};"
                 : "+f"(c[0]), "+f"(c[1]), "+f"(c[2]), "+f"(c[3]) : "r"(a[0]), "r"(a[1]), "r"(a[2]), "r"(a[3]), "r"(b0), "r"(b1));
}
__device__ __forceinline__ uint32_t lds32(uint32_t a) { uint32_t v; asm volatile("ld.shared.b32 %0, [%1];" : "=r"(v) : "r"(a) : "memory"); return v; }
__device__ __forceinline__ uint32_t ldsv(uint32_t a) { uint32_t v; asm volatile("ld.volatile.shared.b32 %0, [%1];" : "=r"(v) : "r"(a) : "memory"); return v; }
__device__ __forceinline__ void stsv(uint32_t a, uint32_t v) { asm volatile("st.volatile.shared.b32 [%0], %1;" ::"r"(a), "r"(v) : "memory"); }
__device__ __forceinline__ float ldsf(uint32_t a) { float v; asm volatile("ld.shared.f32 %0, [%1];" : "=f"(v) : "r"(a) : "memory"); return v; }
__device__ __forceinline__ uint4 lds128(uint32_t a) { uint4 v; asm volatile("ld.shared.v4.b32 {%0,%1,%2,%3}, [%4];" : "=r"(v.x), "=r"(v.y), "=r"(v.z), "=r"(v.w) : "r"(a) : "memory"); return v; }
__device__ __forceinline__ void sts16(uint32_t a, uint16_t v) { asm volatile("st.shared.b16 [%0], %1;" ::"r"(a), "h"(v) : "memory"); }
__device__ __forceinline__ void sts32(uint32_t a, uint32_t v) { asm volatile("st.shared.b32 [%0], %1;" ::"r"(a), "r"(v) : "memory"); }
__device__ __forceinline__ void stsf2(uint32_t a, float x, float y) { asm volatile("st.shared.v2.f32 [%0], {%1,%2};" ::"r"(a), "f"(x), "f"(y) : "memory"); }
__device__ __forceinline__ void sts128(uint32_t a, uint4 v) { asm volatile("st.shared.v4.b32 [%0], {%1,%2,%3,%4};" ::"r"(a), "r"(v.x), "r"(v.y), "r"(v.z), "r"(v.w) : "memory"); }
__device__ __forceinline__ uint16_t f2bf(float x) { return __bfloat16_as_ushort(__float2bfloat16_rn(x)); }
__device__ __forceinline__ float bfround(float x) { return __bfloat162float(__float2bfloat16_rn(x)); }
__device__ __forceinline__ uint32_t pack2(float lo, float hi) { uint32_t r; asm("cvt.rn.bf16x2.f32 %0, %1, %2;" : "=r"(r) : "f"(hi), "f"(lo)); return r; }
__device__ __forceinline__ float ex2(float x) { float r; asm("ex2.approx.ftz.f32 %0, %1;" : "=f"(r) : "f"(x)); return r; }
__device__ __forceinline__ float lg2(float x) { float r; asm("lg2.approx.ftz.f32 %0, %1;" : "=f"(r) : "f"(x)); return r; }

__device__ __forceinline__ float rcp(float x) { float r; asm("rcp.approx.ftz.f32 %0, %1;" : "=f"(r) : "f"(x)); return r; }

__device__ __forceinline__ uint32_t gtime() { uint32_t t; asm volatile("mov.u32 %0, %globaltimer_lo;" : "=r"(t)::"memory"); return t; }
__device__ __forceinline__ void sleep_ns(uint32_t ns) {
    uint32_t t0, t;
    asm volatile("mov.u32 %0, %clock;" : "=r"(t0));
    do { __nanosleep(200); asm volatile("mov.u32 %0, %clock;" : "=r"(t)); } while (t - t0 < 2 * ns);
}

__device__ __forceinline__ void ll_store2(ulonglong2* p, float a, float b, uint32_t tag) {
    unsigned long long x = ((unsigned long long)tag << 32) | __float_as_uint(a);
    unsigned long long y = ((unsigned long long)tag << 32) | __float_as_uint(b);
    asm volatile("st.relaxed.gpu.global.v2.b64 [%0], {%1,%2};" ::"l"(p), "l"(x), "l"(y) : "memory");
}
__device__ __forceinline__ void ll_ld2(const void* p, unsigned long long& x, unsigned long long& y) {
    asm volatile("ld.relaxed.gpu.global.v2.b64 {%0,%1}, [%2];" : "=l"(x), "=l"(y) : "l"(p) : "memory");
}
template <int N>
__device__ __forceinline__ void ll_gather4(const ulonglong2* p, uint32_t tag, float (&r)[N][2]) {
    unsigned long long x[N][4], y[N][4]; uint32_t it = 0;
    while (true) {
        bool ok = true;
#pragma unroll
        for (int k = 0; k < 4 * N; k++) ll_ld2(p + ((k >> 2) * 64 + (k & 3)) * 128, x[k >> 2][k & 3], y[k >> 2][k & 3]);
#pragma unroll
        for (int k = 0; k < 4 * N; k++) ok = ok && (uint32_t)(x[k >> 2][k & 3] >> 32) == tag && (uint32_t)(y[k >> 2][k & 3] >> 32) == tag;
        if (ok) break;
        if (++it > SPIN_MAX) __trap();
        __nanosleep(BACKOFF);
    }
#pragma unroll
    for (int n = 0; n < N; n++) {
        r[n][0] = (__uint_as_float((uint32_t)x[n][0]) + __uint_as_float((uint32_t)x[n][1])) + (__uint_as_float((uint32_t)x[n][2]) + __uint_as_float((uint32_t)x[n][3]));
        r[n][1] = (__uint_as_float((uint32_t)y[n][0]) + __uint_as_float((uint32_t)y[n][1])) + (__uint_as_float((uint32_t)y[n][2]) + __uint_as_float((uint32_t)y[n][3]));
    }
}
__device__ __forceinline__ void cnt_rendezvous(unsigned* c, uint32_t target, int tsk) {
    TS(tsk);
    asm volatile("red.release.gpu.global.add.u32 [%0], 1;" ::"l"(c) : "memory");
    if (tsk == 18) TS(tsk + 1);
    uint32_t v, it = 0;
    while (true) {
        asm volatile("ld.acquire.gpu.global.u32 %0, [%1];" : "=r"(v) : "l"(c) : "memory");
        if ((int)(v - target) >= 0) break;
        if (++it > SPIN_MAX) __trap();
        __nanosleep(BACKOFF_RV);
    }
    asm volatile("fence.proxy.async.global;" ::: "memory");
}

__device__ __forceinline__ void matvec_loadA(uint32_t (&a)[8][4], uint32_t tile, uint32_t bar, int w, int lane) {
    const int i = lane >> 3, rr = lane & 7, chunk = 2 * w + (i & 1);
    const uint32_t a0 = tile + (chunk >> 3) * 8192 + (rr + 8 * (i >> 1)) * 128 + (((chunk & 7) ^ rr) << 4);
#pragma unroll
    for (int hh = 0; hh < 2; hh++) {
        mbar_wait(bar + hh * 8, 0);
#pragma unroll
        for (int k = 0; k < 4; k++) ldsm4t(a[hh * 4 + k], a0 + hh * CH + k * 2048);
    }
}
__device__ __forceinline__ void matvec_mma(float (&c)[4], const uint32_t (&a)[8][4], uint32_t vec, int nvec, int lane) {
    const uint32_t va = vec + (lane & (nvec - 1)) * VROW + (lane >> 3) * 16;
    float d[4][4];
#pragma unroll
    for (int q = 0; q < 4; q++) {
        uint32_t b[4];
        ldsm4(b, va + q * 64);
        d[q][0] = d[q][1] = d[q][2] = d[q][3] = 0.f;
        mma(d[q], a[2 * q], b[0], b[1]);
        mma(d[q], a[2 * q + 1], b[2], b[3]);
    }
#pragma unroll
    for (int k = 0; k < 4; k++) c[k] = (d[0][k] + d[1][k]) + (d[2][k] + d[3][k]);
}
__device__ __forceinline__ void matvecT(float (&c)[4], uint32_t tile, uint32_t vec, int nvec, uint32_t bar, int w, int lane) {
    uint32_t a[8][4];
    matvec_loadA(a, tile, bar, w, lane);
    matvec_mma(c, a, vec, nvec, lane);
}
template <class T> __device__ __forceinline__ T* pin(T* p) { asm volatile("" : "+l"(p)); return p; }
__device__ __forceinline__ void post(uint32_t* p, float v) {
    asm volatile("red.relaxed.gpu.global.add.u32 [%0], %1;" ::"l"(p), "r"(~__float_as_uint(v)) : "memory");
}
__device__ __forceinline__ void ld4_if(const void* p, uint4& x, bool need) {
    asm volatile("{\n.reg .pred q;\nsetp.ne.u32 q, %5, 0;\n@q ld.relaxed.gpu.global.v4.b32 {%0,%1,%2,%3}, [%4];\n}"
                 : "+r"(x.x), "+r"(x.y), "+r"(x.z), "+r"(x.w) : "l"(p), "r"((uint32_t)need) : "memory");
}
__device__ __forceinline__ void gather_o(const uint32_t* e5, int b, int q, int cta, int lane, uint32_t sm, uint32_t backoff) {
    const int r0 = (b * 32 + q * 4 + (cta >> 5)) * 8;
    const uint32_t* p = e5 + (r0 + (lane >> 4) * 4) * 128 + (cta >> 4 & 1) * 64 + (lane & 15) * 4;
    const uint32_t* pl = e5 + 4 * NCTA * 128 + r0 + (lane >> 4) * 4;
    uint4 x[5];
    bool need[5] = {true, true, true, true, true};
    uint32_t it = 0;
    while (true) {
#pragma unroll
        for (int k = 0; k < 5; k++) ld4_if(k < 4 ? p + k * 128 : pl, x[k], need[k]);
#pragma unroll
        for (int k = 0; k < 5; k++) need[k] = !x[k].x || !x[k].y || !x[k].z || !x[k].w;
        if (!__any_sync(0xffffffffu, need[0] | need[1] | need[2] | need[3] | need[4])) break;
        if (++it > SPIN_MAX) __trap();
        if (backoff) __nanosleep(backoff);
    }
    float e[4] = {__uint_as_float(~x[4].x), __uint_as_float(~x[4].y), __uint_as_float(~x[4].z), __uint_as_float(~x[4].w)};
    float mx = fmaxf(fmaxf(e[0], e[1]), fmaxf(e[2], e[3]));
    mx = fmaxf(mx, __shfl_xor_sync(0xffffffffu, mx, 16));
    float o[5] = {0.f, 0.f, 0.f, 0.f, 0.f};
#pragma unroll
    for (int k = 0; k < 4; k++) {
        e[k] = ex2(e[k] - mx);
        o[0] += e[k] * __uint_as_float(~x[k].x); o[1] += e[k] * __uint_as_float(~x[k].y);
        o[2] += e[k] * __uint_as_float(~x[k].z); o[3] += e[k] * __uint_as_float(~x[k].w);
        o[4] += e[k];
    }
#pragma unroll
    for (int k = 0; k < 5; k++) o[k] += __shfl_xor_sync(0xffffffffu, o[k], 16);
    const float r = rcp(o[4]);
    sts32(sm + OFF_Y + b * YROW + (q >> 1) * YHEAD + (q & 1) * 128 + (lane & 15) * 8 + (lane >> 4) * 4,
          lane < 16 ? pack2(o[0] * r, o[1] * r) : pack2(o[2] * r, o[3] * r));
}

__global__ void __launch_bounds__(NTHREADS, 1)
fused_decode_kernel(const char* __restrict__ wqraw, Scratch* const sc, const __nv_bfloat16* __restrict__ xA, const __nv_bfloat16* __restrict__ xB,
                    const char* __restrict__ Kc, const char* __restrict__ Vc, const __grid_constant__ Maps maps,
                    const char* __restrict__ woA, const char* __restrict__ woB, __nv_bfloat16* __restrict__ out, const uint32_t zero) {
    unsigned* const cnt = sc->cnt;
    asm volatile("{\n.reg .pred p;\nsetp.eq.u32 p, %1, 0;\n@p cp.async.bulk.prefetch.L2.global [%0], %2;\n}"
                 ::"l"(wqraw + (size_t)blockIdx.x * (2 * CH)), "r"(threadIdx.x), "n"(CH) : "memory");
    extern __shared__ char smem_raw[];
    const uint32_t sm = ((uint32_t)__cvta_generic_to_shared(smem_raw) + 1023u) & ~1023u;
    if (threadIdx.x == 64) {
        unsigned epoch;
        asm volatile("atom.relaxed.gpu.global.add.u32 %0, [%1], 1;" : "=r"(epoch) : "l"(cnt) : "memory");
        sts32(sm + OFF_TAG, (epoch >> 7) + 1u);
    }
    const uint32_t bars = sm + OFF_BAR;
    const int cta = blockIdx.x, h = cta >> 2, j = cta & 3;
    uint64_t pol = 0;
    if (threadIdx.x == 0) {
        TS(0);
        asm volatile("createpolicy.fractional.L2::evict_first.b64 %0, 1.0;" : "=l"(pol));
#pragma unroll
        for (int i = 0; i < WIN; i++) mbar_init(bars + (B_WQB + i) * 8, 1);
        asm volatile("fence.mbarrier_init.release.cluster;" ::: "memory");
#pragma unroll
        for (int i = 0; i < WIN; i++) {
            mbar_expect(bars + (B_WQB + i) * 8, CH);
            tma3d(sm + OFF_S0 + i * CH, &maps.wqB + (i >> 1), j * 128 + (i & 1) * 64, h * 2, bars + (B_WQB + i) * 8, pol);
        }
    }
    const int tid = threadIdx.x < 64 ? threadIdx.x + 384 : threadIdx.x - 64, warp = tid >> 5, lane = tid & 31;

    if (warp == 12) {
        const char* kp = Kc + (size_t)cta * (8 * CH);
        const char* vp = Vc + (size_t)cta * (8 * CH);
        __syncwarp();
        bar_arrive(0, NTHREADS);
        bar_sync(3, 64);
        if (lane == 0) {
            uint32_t pb[WHI];
#pragma unroll
            for (int i = 0; i < WHI; i++) pb[i] = i < WHI - WIN ? (bars + B_WO * 8) | 1u : bars + (B_WQB + i - (WHI - WIN)) * 8;
            auto pace = [&](uint32_t bar, uint32_t par) {
                uint32_t it = 0;
                while (true) {
                    const uint32_t win = ldsv(sm + OFF_WIN);
                    uint32_t busy = 0;
#pragma unroll
                    for (int i = 0; i < WHI; i++) busy += mbar_test(pb[i] & ~1u, pb[i] & 1u) ^ 1u;
                    if (busy < win) break;
                    if (++it > SPIN_MAX) __trap();
                }
#pragma unroll
                for (int i = 0; i + 1 < WHI; i++) pb[i] = pb[i + 1];
                pb[WHI - 1] = bar | par;
            };
            auto side = [&](const CUtensorMap* m, uint32_t dst, int bidx, int c1, int c2) {
                const uint32_t bar = bars + bidx * 8;
                pace(bar, 0);
                mbar_expect(bar, CH);
                tma3d(dst, m, c1, c2, bar, pol);
            };
#pragma unroll 1
            for (int i = WIN; i < 6; i++)
                side(&maps.wqB + (i >> 1), sm + OFF_S0 + i * CH, B_WQB + i, j * 128 + (i & 1) * 64, h * 2);
            TS(1);
            uint32_t slot = 0, use = 0;
            int nuv = 0;
#pragma unroll 1
            for (int n = 0; n < 2 * NTILE; n++) {
                if (n == RING) {
                    mbar_wait(bars + B_FREE * 8, 0);
#pragma unroll 1
                    for (int q = 0; q < 4; q++) side(&maps.ckv, sm + OFF_S0 + q * CH, B_CKV + q, cta * 64 + q * 16, 0);
                }
                if (nuv < 2 && n > RING && (n >= 2 * NTILE - 8 || mbar_test(bars + B_FREE * 8, 1))) {
                    mbar_wait(bars + B_FREE * 8, 1);
                    side(&maps.wuv, sm + OFF_S1 + nuv * CH, B_WUV + nuv, j * 128 + nuv * 64, h * 2);
                    nuv++;
                }
                const uint32_t fb = bars + slot * 8;
                pace(fb, use & 1);
                mbar_wait(fb + B_EMPTY * 8, (use & 1) ^ 1);
                mbar_expect(fb, CH);
                bulk1d(sm + OFF_RING + slot * CH, ((n & 8) ? vp : kp) + (size_t)((n >> 4) * (8 * NCTA) + (n & 7)) * CH, fb, pol);
                if (n >= FINE_V || (n & 1)) {
                    asm volatile("red.relaxed.gpu.global.add.u32 [%0], %1;" ::"l"(cnt + 3), "r"(n >= FINE_V ? 1 : 2) : "memory");
                    stsv(sm + OFF_NOW, n + 1);
                }
                if (++slot == RING) { slot = 0; use++; }
            }
            TS(2);
            mbar_wait(bars + B_FREE * 8, 0);
            const char* wp = ((cta & 1) ? woB : woA) + (cta >> 1) * 8192;
            uint32_t it = 0;
#pragma unroll 1
            for (int q = 0; q <= 8; q++) {
                const uint32_t bar = bars + (B_WO + q - 1) * 8;
                if (q) mbar_expect(bar, CH / 2);
                while (true) {
                    const uint32_t t0 = ldsv(sm + OFF_TBOX);
                    if (t0 && gtime() - t0 + 16384u >= 16384u + q * BOX_NS) break;
                    if (++it > SPIN_MAX) __trap();
                }
                if (q < 8) asm volatile("cp.async.bulk.prefetch.L2.global.L2::cache_hint [%0], %1, %2;" ::"l"(wp + q * 524288), "n"(CH / 2), "l"(pol) : "memory");
                if (q) tma3d(sm + OFF_S0 + (q - 1) * (CH / 2), &maps.woA + (cta & 1), (q - 1) * 512 + (cta >> 4) * 64, (cta >> 1) & 7, bar, pol);
            }
            TS(3);
        }
    } else if (warp == 13) {
        if (lane == 0) {
#pragma unroll
            for (int i = 0; i < NBAR; i++)
                if (i < B_WQB || i >= B_WQB + WIN)
                    mbar_init(bars + i * 8, i == B_FREE ? 8 : (i >= B_EMPTY && i < B_EMPTY + RING) ? 4 : 1);
            asm volatile("fence.mbarrier_init.release.cluster;" ::: "memory");
#pragma unroll
            for (int i = 2; i < 8; i++) asm volatile("prefetch.tensormap [%0];" ::"l"(&maps.wqB + i) : "memory");
            stsv(sm + OFF_NOW, 0); stsv(sm + OFF_WIN, WIN); stsv(sm + OFF_TBOX, 0);
        }
        __syncwarp();
        bar_arrive(3, 64);
        bar_sync(0, NTHREADS);
        if (lane == 0) {
            const uint32_t base = (lds32(sm + OFF_TAG) - 1u) * (NCTA * 2 * NTILE);
            mbar_wait(bars + (B_WUK + 1) * 8, 0);
            uint32_t it = 0, tbox = 0;
            while (true) {
                const uint32_t n = ldsv(sm + OFF_NOW);
                uint32_t v;
                asm volatile("ld.relaxed.gpu.global.u32 %0, [%1];" : "=r"(v) : "l"(cnt + 3) : "memory");
                v -= base;
                if (v >= NCTA * EST_FROM && (v <= NCTA * EST_TO || !tbox)) {
                    const uint32_t est = (gtime() + (NCTA * 2 * NTILE - v) * BOX_NS / 64 + (uint32_t)(BOX_SHIFT + (~cta & 1) * (BOX_NS / 2))) | 1u;
                    if (!tbox || (int)(est - tbox) < 0) { tbox = est; stsv(sm + OFF_TBOX, est); }
                }
                if (v >= NCTA * 2 * NTILE - GATE_W) break;
                const int diff = (int)(n * NCTA) - (int)v;
                stsv(sm + OFF_WIN, diff < -THETA ? WHI : WIN - (diff > THETA) - (v >= NCTA * END_V));
                if (++it > SPIN_MAX) __trap();
                __nanosleep(v < NCTA * FINE_V ? BACKOFF3 : BACKOFF2);
            }
            stsv(sm + OFF_WIN, WHI);
            TS(24);
        }
    } else if (warp < 4) {
        const int g = lane >> 2, t = lane & 3, i = lane >> 3, rr = lane & 7;
        bar_sync(0, NTHREADS);
        const uint32_t tag = lds32(sm + OFF_TAG);
        {
            mbar_wait(bars + 8, 0);
            float q[2][2];
            ll_gather4<2>(&sc->e1[0][(cta >> 3) * 4][tid], tag, q);
#pragma unroll
            for (int k = 0; k < 4; k++) sts16(sm + OFF_QB + k * 256 + tid * 2, f2bf(q[k & 1][k >> 1]));
        }
        bar_sync(1, 128);
        if (tid == 0) TS(4);
        const bool diag = (t == (g >> 1));
        const uint32_t krow = sm + OFF_RING + (warp * 16 + rr + 8 * (i & 1)) * 256 + (i >> 1) * 128;
        const uint32_t vrow = sm + OFF_RING + (warp * 16 + rr + 8 * (i >> 1)) * 256 + (i & 1) * 128;
        uint32_t slot = 0, ph = 0;
        uint32_t* const e5 = pin(&sc->e5[0][0]);
        float o0 = 0.f, lse0 = 0.f;
#pragma unroll 1
        for (int sg = 0; sg < 4; sg++) {
            uint32_t a[8][4], qf[8][2];
#pragma unroll
            for (int c = 0; c < 8; c++) {
                const uint32_t qa = sm + OFF_QB + sg * 256 + (((c + g) & 7) * 8 + 2 * t) * 2;
                qf[c][0] = lds32(qa); qf[c][1] = lds32(qa + 128);
            }
            float sc8[8][2];
#pragma unroll 1
            for (int tile = 0; tile < 8; tile++) {
                mbar_wait(bars + slot * 8, ph);
#pragma unroll
                for (int c = 0; c < 8; c++) ldsm4(a[c], krow + slot * CH + (((c + rr) & 7) << 4));
                __syncwarp();
                if (lane == 0) mbar_arrive(bars + (B_EMPTY + slot) * 8 + ((a[0][0] | a[1][0] | a[2][0] | a[3][0] | a[4][0] | a[5][0] | a[6][0] | a[7][0]) & zero));
                if (++slot == RING) { slot = 0; ph ^= 1; }
                float s0[4] = {0.f, 0.f, 0.f, 0.f}, s1[4] = {0.f, 0.f, 0.f, 0.f};
#pragma unroll
                for (int c = 0; c < 8; c += 2) { mma(s0, a[c], qf[c][0], qf[c][1]); mma(s1, a[c + 1], qf[c + 1][0], qf[c + 1][1]); }
                const float slo = (g & 1) ? s0[1] + s1[1] : s0[0] + s1[0];
                const float shi = (g & 1) ? s0[3] + s1[3] : s0[2] + s1[2];
#pragma unroll
                for (int k = 0; k < 7; k++) { sc8[k][0] = sc8[k + 1][0]; sc8[k][1] = sc8[k + 1][1]; }
                sc8[7][0] = diag ? bfround(bfround(slo) * SCALE) : -INFINITY;
                sc8[7][1] = diag ? bfround(bfround(shi) * SCALE) : -INFINITY;
            }
            float m = fmaxf(sc8[0][0], sc8[0][1]);
#pragma unroll
            for (int k = 1; k < 8; k++) m = fmaxf(m, fmaxf(sc8[k][0], sc8[k][1]));
            int key = __float_as_int(m);
            key ^= (key >> 31) & 0x7fffffff;
            key = __reduce_max_sync(0xffffffffu, key);
            key ^= (key >> 31) & 0x7fffffff;
            m = __int_as_float(key);
            float l = 0.f;
            uint32_t pf[8][2];
#pragma unroll
            for (int k = 0; k < 8; k++) {
                const float plo = ex2((sc8[k][0] - m) * LOG2E), phi = ex2((sc8[k][1] - m) * LOG2E);
                l += plo + phi;
                pf[k][0] = (g & 1) ? pack2(0.f, plo) : pack2(plo, 0.f);
                pf[k][1] = (g & 1) ? pack2(0.f, phi) : pack2(phi, 0.f);
            }
#pragma unroll
            for (int o = 16; o; o >>= 1) l += __shfl_xor_sync(0xffffffffu, l, o);
            if (lane == 0) stsf2(sm + OFF_ML + warp * 8, m, l);
            bar_sync(1, 128);
            const uint4 ml0 = lds128(sm + OFF_ML), ml1 = lds128(sm + OFF_ML + 16);
            const float m0 = __uint_as_float(ml0.x), m1 = __uint_as_float(ml0.z), m2 = __uint_as_float(ml1.x), m3 = __uint_as_float(ml1.z);
            const float M = fmaxf(fmaxf(m0, m1), fmaxf(m2, m3));
            const float L = (ex2((m0 - M) * LOG2E) * __uint_as_float(ml0.y) + ex2((m1 - M) * LOG2E) * __uint_as_float(ml0.w))
                          + (ex2((m2 - M) * LOG2E) * __uint_as_float(ml1.y) + ex2((m3 - M) * LOG2E) * __uint_as_float(ml1.w));
            const float f = ex2((m - M) * LOG2E) * rcp(L);
            const float lse = M * LOG2E + lg2(L);
            if (sg == 1) {
                mbar_wait(bars + B_RV * 8, 0);
                post(e5 + cta * 128 + tid, o0);
                if (tid == 0) post(e5 + 4 * NCTA * 128 + cta, lse0);
            }
            if (sg == 0) lse0 = lse;
            else if (tid == 0) post(e5 + (4 * NCTA + sg) * 128 + cta, lse);
            float acc[8][4];
#pragma unroll
            for (int c = 0; c < 8; c++) { acc[c][0] = acc[c][1] = acc[c][2] = acc[c][3] = 0.f; }
#pragma unroll 1
            for (int tile = 0; tile < 8; tile++) {
                const uint32_t b0 = pf[0][0], b1 = pf[0][1];
#pragma unroll
                for (int k = 0; k < 7; k++) { pf[k][0] = pf[k + 1][0]; pf[k][1] = pf[k + 1][1]; }
                mbar_wait(bars + slot * 8, ph);
#pragma unroll
                for (int c = 0; c < 8; c++) ldsm4t(a[c], vrow + slot * CH + (((c + rr) & 7) << 4));
#pragma unroll
                for (int c = 0; c < 8; c++) mma(acc[c], a[c], b0, b1);
                __syncwarp();
                if (lane == 0) mbar_arrive(bars + (B_EMPTY + slot) * 8 + ((a[0][0] | a[1][0] | a[2][0] | a[3][0] | a[4][0] | a[5][0] | a[6][0] | a[7][0]) & zero));
                if (++slot == RING) { slot = 0; ph ^= 1; }
            }
            if (tid == 0) TS(5);
            float v[2][8];
#pragma unroll
            for (int c = 0; c < 8; c++) { v[0][c] = acc[c][0] + acc[(c + 7) & 7][1]; v[1][c] = acc[c][2] + acc[(c + 7) & 7][3]; }
#pragma unroll
            for (int c = 0; c < 4; c++) { v[0][c] += __shfl_xor_sync(0xffffffffu, v[0][c + 4], 2); v[1][c] += __shfl_xor_sync(0xffffffffu, v[1][c + 4], 2); }
            const int src = (lane & ~3) | ((lane + 3) & 3);
#pragma unroll
            for (int c = 0; c < 2; c++) { v[0][c] += __shfl_sync(0xffffffffu, v[0][c + 2], src); v[1][c] += __shfl_sync(0xffffffffu, v[1][c + 2], src); }
            const uint32_t wa = sm + OFF_RED + (warp * 160 + 16 * t + 8 * (t >> 1) + g) * 4;
            sts32(wa, __float_as_uint(v[0][0] * f)); sts32(wa + 32, __float_as_uint(v[0][1] * f));
            sts32(wa + 320, __float_as_uint(v[1][0] * f)); sts32(wa + 352, __float_as_uint(v[1][1] * f));
            bar_sync(1, 128);
            const uint32_t ra = sm + OFF_RED + (tid + warp * 8) * 4;
            const float o = (ldsf(ra) + ldsf(ra + 640)) + (ldsf(ra + 1280) + ldsf(ra + 1920));
            if (sg == 0) o0 = o;
            else post(e5 + (sg * NCTA + cta) * 128 + tid, o);
        }
        if (tid == 0) TS(6);
        if (cta & 1) {
            gather_o(e5, 1, 4 + warp, cta, lane, sm, 0);
            bar_arrive(4, 256 + 128);
        }
        if (tid == 0) TS(16);
    } else {
        const int st = tid - 128, w = warp - 4;
        const int g = lane >> 2, t = lane & 3, i = lane >> 3, rr = lane & 7;
        if (st < 64) {
            const int which = st >> 5, b = (st >> 4) & 1, c = st & 15;
            const uint4 v = __ldg((const uint4*)((which ? xA : xB) + b * 512 + j * 128) + c);
            sts128(sm + OFF_XB + (which * 2 + b) * VROW + c * 16, v);
        }
        bar_sync(0, NTHREADS);
        const uint32_t tag = lds32(sm + OFF_TAG);
        float c[4];
#pragma unroll 1
        for (int which = 0; which < 2; which++) {
            matvecT(c, sm + OFF_S0 + which * 2 * CH, sm + OFF_XB + which * 2 * VROW, 2, bars + (B_WQB + which * 2) * 8, w, lane);
            if (t == 0) {
                ll_store2(&sc->e1[which][cta][w * 16 + g], c[0], c[1], tag);
                ll_store2(&sc->e1[which][cta][w * 16 + g + 8], c[2], c[3], tag);
            }
        }
        __syncwarp();
        if (lane == 0) mbar_arrive(bars + B_FREE * 8);
        if (st == 0) TS(8);
        if (st < 128) {
            float q[1][2];
            sleep_ns(POLL_DELAY);
            ll_gather4<1>(&sc->e1[1][h * 4][st], tag, q);
            sts16(sm + OFF_QA + st * 2, f2bf(q[0][0])); sts16(sm + OFF_QA + VROW + st * 2, f2bf(q[0][1]));
        } else {
            const int u = st - 128;
            ((uint4*)sc->e5[(u >> 5) * NCTA + cta])[u & 31] = make_uint4(0, 0, 0, 0);
            ((uint2*)sc->e4[cta])[u] = make_uint2(0, 0);
            if (cta == 0) ((uint4*)sc->e5[4 * NCTA])[u] = make_uint4(0, 0, 0, 0);
            if (u < 8) ((uint32_t*)out)[cta * 8 + u] = 0u;
        }
        bar_sync(2, 256);
        if (st == 0) TS(9);
        {
            const int row = w * 16 + rr + 8 * (i & 1);
            const uint32_t a0 = sm + OFF_S2 + (row >> 6) * CH + (row & 63) * 128;
            const uint32_t va = sm + OFF_QA + g * VROW + t * 4;
            float d[4] = {0.f, 0.f, 0.f, 0.f};
            c[0] = c[1] = c[2] = c[3] = 0.f;
            mbar_wait(bars + (B_WUK + (w >> 2)) * 8, 0);
#pragma unroll
            for (int ks = 0; ks < 8; ks++) {
                const int chunk = 2 * ks + (i >> 1);
                uint32_t a[4];
                ldsm4(a, a0 + (chunk >> 3) * 8192 + (((chunk & 7) ^ rr) << 4));
                const uint32_t b0 = (g < 2) ? lds32(va + ks * 32) : 0u, b1 = (g < 2) ? lds32(va + ks * 32 + 16) : 0u;
                if (ks & 1) mma(d, a, b0, b1); else mma(c, a, b0, b1);
            }
            if (t == 0) {
                const uint32_t qs = sm + OFF_QS + (w * 16 + g) * 2;
                sts16(qs, f2bf(c[0] + d[0])); sts16(qs + VROW, f2bf(c[1] + d[1]));
                sts16(qs + 16, f2bf(c[2] + d[2])); sts16(qs + VROW + 16, f2bf(c[3] + d[3]));
            }
            bar_sync(2, 256);
            if (w == 0) {
                const int b = lane >> 4, cc = lane & 15;
                sc->qabs[(b * 32 + h) * 64 + ((j * 16 + cc) ^ (h & 7))] = lds128(sm + OFF_QS + b * VROW + cc * 16);
                __syncwarp();
                if (lane == 0) {
                    cnt_rendezvous(cnt + 1, tag * 128u, 18);
                    TS(10);
                    mbar_arrive(bars + B_RV * 8);
                    mbar_expect(bars + B_GATH * 8, 2 * CH);
                    bulk1d_n(sm + OFF_S2, sc->qabs + (cta >> 6) * 2048, 2 * CH, bars + B_GATH * 8);
                }
                __syncwarp();
            }
        }
        mbar_wait(bars + B_GATH * 8, 0);
        if (st == 0) TS(11);
        {
            const int mt = w & 1, kg = w >> 1;
            const uint32_t qa = sm + OFF_S2 + (mt * 16 + rr + 8 * (i & 1)) * 1024;
            const uint32_t ka = sm + OFF_S0 + kg * CH + (rr + 8 * (i >> 1)) * 128;
            float s0[4] = {0.f, 0.f, 0.f, 0.f}, s1[4] = {0.f, 0.f, 0.f, 0.f};
            mbar_wait(bars + (B_CKV + kg) * 8, 0);
#pragma unroll 2
            for (int gq = 0; gq < 8; gq++) {
#pragma unroll
                for (int k4 = 0; k4 < 4; k4++) {
                    uint32_t a[4], b[4];
                    ldsm4(a, qa + gq * 128 + (((2 * k4 + (i >> 1)) ^ rr) << 4));
                    ldsm4(b, ka + gq * 2048 + (((2 * k4 + (i & 1)) ^ rr) << 4));
                    mma(s0, a, b[0], b[1]);
                    mma(s1, a, b[2], b[3]);
                }
            }
            const uint32_t sa = sm + OFF_SC + ((mt * 16 + g) * 68 + kg * 16 + 2 * t) * 4;
            stsf2(sa, s0[0], s0[1]); stsf2(sa + 32, s1[0], s1[1]);
            stsf2(sa + 8 * 68 * 4, s0[2], s0[3]); stsf2(sa + 8 * 68 * 4 + 32, s1[2], s1[3]);
        }
        bar_sync(2, 256);
        {
            const int head = w * 4 + i;
            const uint32_t sa = sm + OFF_SC + (head * 68 + rr * 8) * 4;
            const uint4 u0 = lds128(sa), u1 = lds128(sa + 16);
            float s[8] = {__uint_as_float(u0.x), __uint_as_float(u0.y), __uint_as_float(u0.z), __uint_as_float(u0.w),
                          __uint_as_float(u1.x), __uint_as_float(u1.y), __uint_as_float(u1.z), __uint_as_float(u1.w)};
            float mx = s[0];
#pragma unroll
            for (int k = 1; k < 8; k++) mx = fmaxf(mx, s[k]);
#pragma unroll
            for (int o = 1; o < 8; o <<= 1) mx = fmaxf(mx, __shfl_xor_sync(0xffffffffu, mx, o));
            float sum = 0.f;
#pragma unroll
            for (int k = 0; k < 8; k++) { s[k] = ex2((s[k] - mx) * (SCALE * LOG2E)); sum += s[k]; }
#pragma unroll
            for (int o = 1; o < 8; o <<= 1) sum += __shfl_xor_sync(0xffffffffu, sum, o);
            const float inv = __fdividef(1.f, sum);
            uint4 p;
            p.x = pack2(s[0] * inv, s[1] * inv); p.y = pack2(s[2] * inv, s[3] * inv);
            p.z = pack2(s[4] * inv, s[5] * inv); p.w = pack2(s[6] * inv, s[7] * inv);
            sts128(sm + OFF_P + head * 128 + ((rr ^ (head & 7)) << 4), p);
            if (rr == 0) ((float*)sc->lse)[head * 128 + cta] = mx * (SCALE * LOG2E) + lg2(sum);
        }
        bar_sync(2, 256);
        {
            float o[2][8][4];
#pragma unroll
            for (int mt = 0; mt < 2; mt++)
#pragma unroll
                for (int n = 0; n < 8; n++) { o[mt][n][0] = o[mt][n][1] = o[mt][n][2] = o[mt][n][3] = 0.f; }
            const uint32_t pa = sm + OFF_P + (rr + 8 * (i & 1)) * 128;
            const uint32_t va = sm + OFF_S0 + w * 2048 + (rr + 8 * (i & 1)) * 128;
#pragma unroll 1
            for (int kq = 0; kq < 4; kq++) {
                uint32_t a0[4], a1[4];
                ldsm4(a0, pa + (((2 * kq + (i >> 1)) ^ rr) << 4));
                ldsm4(a1, pa + 2048 + (((2 * kq + (i >> 1)) ^ rr) << 4));
#pragma unroll
                for (int n = 0; n < 8; n += 2) {
                    uint32_t b[4];
                    ldsm4t(b, va + kq * CH + (((n + (i >> 1)) ^ rr) << 4));
                    mma(o[0][n], a0, b[0], b[1]); mma(o[1][n], a1, b[0], b[1]);
                    mma(o[0][n + 1], a0, b[2], b[3]); mma(o[1][n + 1], a1, b[2], b[3]);
                }
            }
#pragma unroll
            for (int mt = 0; mt < 2; mt++)
#pragma unroll
                for (int hf = 0; hf < 2; hf++) {
                    const uint32_t dst = sm + OFF_S2 + (mt * 16 + hf * 8 + g) * 1024 + w * 128 + t * 16;
#pragma unroll
                    for (int nb = 0; nb < 2; nb++) {
                        uint4 v;
                        v.x = pack2(o[mt][nb * 4 + 0][hf * 2], o[mt][nb * 4 + 0][hf * 2 + 1]);
                        v.y = pack2(o[mt][nb * 4 + 1][hf * 2], o[mt][nb * 4 + 1][hf * 2 + 1]);
                        v.z = pack2(o[mt][nb * 4 + 2][hf * 2], o[mt][nb * 4 + 2][hf * 2 + 1]);
                        v.w = pack2(o[mt][nb * 4 + 3][hf * 2], o[mt][nb * 4 + 3][hf * 2 + 1]);
                        sts128(dst + nb * 64, v);
                    }
                }
            asm volatile("fence.proxy.async.shared::cta;" ::: "memory");
            __syncwarp();
            if (lane == 0) mbar_arrive(bars + B_FREE * 8);
        }
        bar_sync(2, 256);
        if (st == 0) {
            TS(12);
#pragma unroll 1
            for (int k = 0; k < ST_SPLIT; k++) {
                asm volatile("cp.async.bulk.tensor.3d.global.shared::cta.bulk_group [%0, {%2,%3,%4}], [%1];"
                             ::"l"(&maps.ctxp), "r"(sm + OFF_S2 + k * (2 * CH / ST_SPLIT)), "r"(0), "r"(cta), "r"(k * (128 / ST_SPLIT)) : "memory");
                if (k + 1 < ST_SPLIT) __nanosleep(ST_GAP);
            }
            asm volatile("cp.async.bulk.commit_group;" ::: "memory");
            asm volatile("cp.async.bulk.wait_group 0;" ::: "memory");
            cnt_rendezvous(cnt + 2, tag * 128u, 20);
            TS(13);
            mbar_expect(bars + B_GATH * 8, 2 * CH + 512);
            bulk1d_n(sm + OFF_LSE, sc->lse + h * 32, 512, bars + B_GATH * 8);
#pragma unroll 1
            for (int k = 0; k < ST_SPLIT; k++) {
                bulk1d_n(sm + OFF_S2 + k * (2 * CH / ST_SPLIT), sc->ctxp + cta * 2048 + k * (2048 / ST_SPLIT), 2 * CH / ST_SPLIT, bars + B_GATH * 8);
                __nanosleep(LD_GAP);
            }
        }
        __syncwarp();
        {
            mbar_wait(bars + B_GATH * 8, 1);
            if (st == 0) TS(22);
            uint4 v[8];
#pragma unroll
            for (int k = 0; k < 8; k++) v[k] = lds128(sm + OFF_S2 + (k * 256 + st) * 16);
            float ls[4];
#pragma unroll
            for (int k = 0; k < 4; k++) ls[k] = ldsf(sm + OFF_LSE + (k * 32 + lane) * 4);
            float m0 = fmaxf(ls[0], ls[1]), m1 = fmaxf(ls[2], ls[3]);
#pragma unroll
            for (int o = 16; o; o >>= 1) { m0 = fmaxf(m0, __shfl_xor_sync(0xffffffffu, m0, o)); m1 = fmaxf(m1, __shfl_xor_sync(0xffffffffu, m1, o)); }
            ls[0] = ex2(ls[0] - m0); ls[1] = ex2(ls[1] - m0); ls[2] = ex2(ls[2] - m1); ls[3] = ex2(ls[3] - m1);
            float z0 = ls[0] + ls[1], z1 = ls[2] + ls[3];
#pragma unroll
            for (int o = 16; o; o >>= 1) { z0 += __shfl_xor_sync(0xffffffffu, z0, o); z1 += __shfl_xor_sync(0xffffffffu, z1, o); }
            z0 = __fdividef(1.f, z0); z1 = __fdividef(1.f, z1);
            ls[0] *= z0; ls[1] *= z0; ls[2] *= z1; ls[3] *= z1;
            float a[2][8];
#pragma unroll
            for (int e = 0; e < 8; e++) a[0][e] = a[1][e] = 0.f;
            const int rg = st >> 4;
#pragma unroll
            for (int k = 0; k < 8; k++) {
                const float wt = __shfl_sync(0xffffffffu, ls[k >> 1], rg + 16 * (k & 1));
                const uint32_t u[4] = {v[k].x, v[k].y, v[k].z, v[k].w};
#pragma unroll
                for (int e = 0; e < 4; e++) {
                    a[k >> 2][2 * e] += wt * __uint_as_float(u[e] << 16);
                    a[k >> 2][2 * e + 1] += wt * __uint_as_float(u[e] & 0xffff0000u);
                }
            }
            const int b = lane >> 4, u16 = lane & 15;
            const uint32_t ra = sm + OFF_SC + (w * 256 + b * 128 + (u16 >> 3) * 64 + ((u16 >> 2) & 1) * 32 + (u16 & 3) * 2) * 4;
#pragma unroll
            for (int e = 0; e < 8; e += 2) {
                const float k0 = b ? a[1][e] : a[0][e], k1 = b ? a[1][e + 1] : a[0][e + 1];
                const float s0 = b ? a[0][e] : a[1][e], s1 = b ? a[0][e + 1] : a[1][e + 1];
                stsf2(ra + (e >> 1) * 32, k0 + __shfl_xor_sync(0xffffffffu, s0, 16), k1 + __shfl_xor_sync(0xffffffffu, s1, 16));
            }
            bar_sync(2, 256);
            float s = 0.f;
#pragma unroll
            for (int k = 0; k < 8; k++) s += ldsf(sm + OFF_SC + (k * 256 + st) * 4);
            const float hi = bfround(s);
            const uint32_t ca = sm + OFF_CC + (st >> 7) * VROW + (st & 127) * 2;
            sts16(ca, f2bf(hi)); sts16(ca + 2 * VROW, f2bf(s - hi));
            bar_sync(2, 256);
        }
        matvecT(c, sm + OFF_S1, sm + OFF_CC, 4, bars + B_WUV * 8, w, lane);
#pragma unroll
        for (int k = 0; k < 4; k++) c[k] += __shfl_xor_sync(0xffffffffu, c[k], 1);
        post(&sc->e4[cta][(t & 1) * 128 + w * 16 + (t >> 1) * 8 + g], t == 0 ? c[0] : t == 1 ? c[1] : t == 2 ? c[2] : c[3]);
        __syncwarp();
        if (lane == 0) mbar_arrive(bars + B_FREE * 8);
        if (st == 0) TS(23);
        if (st < 128) sts32(sm + OFF_PAIR + st * 4, EMPTY);
        if (!(cta & 1)) {
            const uint32_t* p = &sc->e4[((w & 6) + (lane >> 4)) * 16 + (cta >> 5) * 4][(w & 1) * 128 + (cta >> 4 & 1) * 64 + (lane & 15) * 4];
            uint4 x[4];
            bool need[4] = {true, true, true, true};
            uint32_t it = 0;
            sleep_ns(POLL_DELAY2);
            while (true) {
#pragma unroll
                for (int q = 0; q < 4; q++) ld4_if(p + q * 256, x[q], need[q]);
#pragma unroll
                for (int q = 0; q < 4; q++) need[q] = !x[q].x || !x[q].y || !x[q].z || !x[q].w;
                if (!__any_sync(0xffffffffu, need[0] | need[1] | need[2] | need[3])) break;
                if (++it > SPIN_MAX) __trap();
                __nanosleep(BACKOFF);
            }
            auto sum4 = [](uint32_t a, uint32_t b, uint32_t c, uint32_t d) {
                return (__uint_as_float(~a) + __uint_as_float(~b)) + (__uint_as_float(~c) + __uint_as_float(~d));
            };
            asm volatile("st.shared.v2.b32 [%0], {%1,%2};" ::"r"(sm + OFF_Y + (w & 1) * YROW + (w >> 1) * YHEAD + lane * 8),
                         "r"(pack2(sum4(x[0].x, x[1].x, x[2].x, x[3].x), sum4(x[0].y, x[1].y, x[2].y, x[3].y))),
                         "r"(pack2(sum4(x[0].z, x[1].z, x[2].z, x[3].z), sum4(x[0].w, x[1].w, x[2].w, x[3].w))) : "memory");
        }
        else {
            sleep_ns(POLL_DELAY2);
            gather_o(sc->e5[0], 0, w, cta, lane, sm, BACKOFF);
            if (w < 4) gather_o(sc->e5[0], 1, w, cta, lane, sm, BACKOFF);
        }
        if (st == 0) TS(14);
        bar_sync(2, 256);
        {
            const int hf = w >> 2, cg = w & 3;
            const uint32_t a0 = sm + OFF_S0 + hf * 8192 + (rr + 8 * (i >> 1)) * 128 + (((2 * cg + (i & 1)) ^ rr) << 4);
            const uint32_t va = sm + OFF_Y + (lane >> 1 & 1) * YROW + (lane & 1) * YHEAD + hf * 128 + i * 16;
            const uint32_t wb = bars + (B_WO + hf) * 8;
            const uint32_t pa = sm + OFF_PAIR + (cg * 32 + lane) * 4;
            const int col = (t & 1) * 1024 + (cta & 1) * 512 + (cta >> 1 & 7) * 64 + cg * 16 + (t >> 1) * 8 + g;
            __nv_bfloat16* const outp = pin(out + (col & ~1));
            const bool up = t >= 2, odd = g & 1;
            uint32_t a[4][4][4], b[4][4];
            float d[2][4][4];
#pragma unroll
            for (int k = 0; k < 8; k++) d[k >> 2][k & 3][0] = d[k >> 2][k & 3][1] = d[k >> 2][k & 3][2] = d[k >> 2][k & 3][3] = 0.f;
            auto load_w = [&](int hd) {
                mbar_wait(wb + hd * 16, 0);
#pragma unroll
                for (int k = 0; k < 4; k++) ldsm4t(a[hd][k], a0 + hd * CH + k * 2048);
            };
            auto load_y = [&](int k) { ldsm4(b[k], va + k * YHEAD); ldsm4(b[k + 1], va + k * YHEAD + 64); };
            auto head = [&](int hd) {
#pragma unroll
                for (int k = 0; k < 4; k++) mma(d[hd & 1][k], a[hd][k], b[(hd & 2) + (k >> 1)][(k & 1) * 2], b[(hd & 2) + (k >> 1)][(k & 1) * 2 + 1]);
            };
            load_y(0);
            load_w(0); head(0);
            load_w(1); head(1);
            if (cta & 1) bar_sync(4, 256 + 128);
            load_y(2);
            if (st == 0) TS(25);
            load_w(2); head(2);
            float z = up ? (d[0][0][2] + d[0][1][2]) + (d[0][2][2] + d[0][3][2]) : (d[0][0][0] + d[0][1][0]) + (d[0][2][0] + d[0][3][0]);
            mbar_wait_uni(wb + 48);
            if (st == 0) TS(26);
            uint32_t other = ldsv(pa);
#pragma unroll
            for (int k = 0; k < 4; k++) ldsm4t(a[3][k], a0 + 3 * CH + k * 2048);
            head(3);
            z += other != EMPTY ? __uint_as_float(other) : 0.f;
            float z1 = z, z3 = z;
#pragma unroll
            for (int k = 0; k < 3; k++) { z1 += d[1][k][1]; z3 += d[1][k][3]; }
            z = up ? z3 + d[1][3][3] : z1 + d[1][3][1];
            if (st == 0) TS(17);
            asm volatile("{\n.reg .pred p;\nsetp.eq.u32 p, %2, %3;\n@p bra FIRST;\nred.relaxed.gpu.global.add.noftz.bf16x2 [%0], %1;\nexit;\nFIRST:\n}"
                         ::"l"(outp), "r"(odd ? pack2(0.f, z) : pack2(z, 0.f)), "r"(other), "n"(EMPTY) : "memory");
            asm volatile("atom.shared.exch.b32 %0, [%1], %2;" : "=r"(other) : "r"(pa), "r"(__float_as_uint(z)) : "memory");
            z += __uint_as_float(other);
            asm volatile("{\n.reg .pred p;\nsetp.eq.u32 p, %2, %3;\n@p exit;\nred.relaxed.gpu.global.add.noftz.bf16x2 [%0], %1;\n}"
                         ::"l"(outp), "r"(odd ? pack2(0.f, z) : pack2(z, 0.f)), "r"(other), "n"(EMPTY) : "memory");
        }
    }
}

typedef CUresult (*EncodeFn)(CUtensorMap*, CUtensorMapDataType, cuuint32_t, void*, const cuuint64_t*, const cuuint64_t*,
                             const cuuint32_t*, const cuuint32_t*, CUtensorMapInterleave, CUtensorMapSwizzle,
                             CUtensorMapL2promotion, CUtensorMapFloatOOBfill);

void make_map(EncodeFn enc, CUtensorMap* m, void* p, unsigned rows, unsigned cols, unsigned br, unsigned bg) {
    cuuint64_t gd[3] = {64, rows, cols / 64};
    cuuint64_t gs[2] = {(cuuint64_t)cols * 2, 128};
    cuuint32_t bx[3] = {64, br, bg};
    cuuint32_t es[3] = {1, 1, 1};
    enc(m, CU_TENSOR_MAP_DATA_TYPE_BFLOAT16, 3, p, gd, gs, bx, es, CU_TENSOR_MAP_INTERLEAVE_NONE,
        CU_TENSOR_MAP_SWIZZLE_128B, CU_TENSOR_MAP_L2_PROMOTION_L2_128B, CU_TENSOR_MAP_FLOAT_OOB_FILL_NONE);
}

}

extern "C" void kernel_launch(void* const* d_in, const int* in_sizes, int n_in, void* d_out, int out_size) {
    static EncodeFn enc = nullptr;
    if (!enc) {
        void* fn = nullptr;
        cudaDriverEntryPointQueryResult qr;
        cudaGetDriverEntryPoint("cuTensorMapEncodeTiled", &fn, cudaEnableDefault, &qr);
        enc = (EncodeFn)fn;
        cudaFuncSetAttribute(fused_decode_kernel, cudaFuncAttributeMaxDynamicSharedMemorySize, SMEM_BYTES);
    }
    Scratch* sc = nullptr;
    cudaGetSymbolAddress((void**)&sc, g_scratch);
    Maps maps;
    make_map(enc, &maps.wqB, d_in[9], 512, 4096, 64, 2);
    make_map(enc, &maps.wqA, d_in[2], 512, 4096, 64, 2);
    make_map(enc, &maps.wuk, d_in[3], 512, 4096, 64, 2);
    make_map(enc, &maps.wuv, d_in[4], 512, 4096, 64, 2);
    make_map(enc, &maps.woA, d_in[5], 4096, 512, 64, 1);
    make_map(enc, &maps.woB, d_in[10], 4096, 512, 64, 1);
    make_map(enc, &maps.ckv, d_in[1], 8192, 512, 16, 8);
    {
        void* p = sc->ctxp;
        cuuint64_t gd[3] = {128, 128, 128};
        cuuint64_t gs[2] = {256, 32768};
        cuuint32_t bx[3] = {128, 1, 128 / ST_SPLIT};
        cuuint32_t es[3] = {1, 1, 1};
        enc(&maps.ctxp, CU_TENSOR_MAP_DATA_TYPE_BFLOAT16, 3, p, gd, gs, bx, es, CU_TENSOR_MAP_INTERLEAVE_NONE,
            CU_TENSOR_MAP_SWIZZLE_NONE, CU_TENSOR_MAP_L2_PROMOTION_NONE, CU_TENSOR_MAP_FLOAT_OOB_FILL_NONE);
    }
    fused_decode_kernel<<<NCTA, NTHREADS, SMEM_BYTES>>>((const char*)d_in[9], sc, (const __nv_bfloat16*)d_in[0], (const __nv_bfloat16*)d_in[6],
                                                         (const char*)d_in[7], (const char*)d_in[8], maps, (const char*)d_in[5], (const char*)d_in[10],
                                                         (__nv_bfloat16*)d_out, 0u);
}
```
